```python
import torch

def _softmax(x, axis=-1):
    return torch.softmax(x, dim=axis)
def _gelu(x):
    return torch.nn.functional.gelu(x, approximate="tanh")
def _silu(x):
    return torch.nn.functional.silu(x)
def _sigmoid(x):
    return torch.sigmoid(x)
def _layernorm(x, axis=-1, eps=1e-5):
    m = x.mean(dim=axis, keepdim=True)
    v = x.var(dim=axis, keepdim=True, unbiased=False)
    return (x - m) / torch.sqrt(v + eps)
def _scatter_add(tgt, idx, src, axis=0):
    return tgt.clone().index_add_(axis, idx, src)
def _segment_sum(src, seg, n):
    out = torch.zeros((n,) + src.shape[1:], dtype=src.dtype)
    return out.index_add_(0, seg, src)
def _pad(x, pw):
    flat = tuple(v for pair in reversed(pw) for v in pair)
    return torch.nn.functional.pad(x, flat)

kernel_name = 'gated_mix__sliding_local_dilated__mixer_token_mlp__prompt'

def setup_inputs():

    _w = (lambda a: (lambda t: t.to(torch.bfloat16) if t.is_floating_point() else t)(torch.as_tensor(a)))
    def _A_setup():
        B, S, D = 1, 2048, 640
        return {
            "x": _w((lambda *s: torch.randn(*s, dtype=torch.bfloat16) * 0.05)(B, S, D)),
            "wqkv": _w((lambda *s: torch.randn(*s, dtype=torch.bfloat16) * 0.8)(D, 3 * D)),
            "wo": _w((lambda *s: torch.randn(*s, dtype=torch.bfloat16) * 0.05)(D, D)),
        }
    _A_in = _A_setup()

    def _B_setup():
        B, S, D, F = 1, 2048, 640, 1536
        return {
            "x": _w((lambda *s: torch.randn(*s, dtype=torch.bfloat16) * 0.05)(B, S, D)),
            "w1": _w((lambda *s: torch.randn(*s, dtype=torch.bfloat16) * 0.8)(S, F) * (S ** -0.5)),
            "b1": _w((lambda *s: torch.randn(*s, dtype=torch.bfloat16) * 0.8)(F) * 0.02),
            "w2": _w((lambda *s: torch.randn(*s, dtype=torch.bfloat16) * 0.8)(F, S) * (F ** -0.5)),
            "b2": _w((lambda *s: torch.randn(*s, dtype=torch.bfloat16) * 0.8)(S) * 0.02),
        }
    _B_in = _B_setup()

    return {
        "A_x": _A_in["x"],
        "A_wqkv": _A_in["wqkv"],
        "A_wo": _A_in["wo"],
        "B_x": _B_in["x"],
        "B_w1": _B_in["w1"],
        "B_b1": _B_in["b1"],
        "B_w2": _B_in["w2"],
        "B_b2": _B_in["b2"],
        "gate_w": _w((lambda *s: torch.randn(*s, dtype=torch.bfloat16) * 0.05)(640) * 16.0),
    }

def reference(A_x, A_wqkv, A_wo, B_x, B_w1, B_b1, B_w2, B_b2, gate_w):
    def _A_ref(x, wqkv, wo):
        B, S, D = x.shape
        H = 32; Dh = D // H
        W, dil = 8, 2
        qkv = (lambda x, *d: x.permute(*d))((x @ wqkv).reshape(B, S, 3, H, Dh), 2, 0, 3, 1, 4)
        q, k, v = qkv[0], qkv[1], qkv[2]
        scale = Dh ** -0.5
        pos = torch.arange(S)
        off = torch.arange(W) * dil
        idx = pos[:, None] - off[None, :]
        mask = idx >= 0
        idx_c = torch.where(mask, idx, 0).reshape(-1)
        kg = k[:, :, idx_c, :].reshape(B, H, S, W, Dh)
        vg = v[:, :, idx_c, :].reshape(B, H, S, W, Dh)
        logits = torch.einsum("bhsd,bhswd->bhsw", q, kg) * scale
        logits = torch.where(mask[None, None, :, :], logits, -1e9)
        attn = _softmax(logits, axis=-1)
        o = torch.einsum("bhsw,bhswd->bhsd", attn, vg)
        return (lambda x, *d: x.permute(*d))(o, 0, 2, 1, 3).reshape(B, S, D) @ wo

    def _B_ref(x, w1, b1, w2, b2):
        B, S, D = x.shape
        h = _layernorm(x, axis=-1)
        u = torch.einsum("bsd,sf->bdf", h, w1) + b1
        u = _gelu(u)
        y = torch.einsum("bdf,fs->bds", u, w2) + b2
        return (lambda x, *d: x.permute(*d))(y, 0, 2, 1)

    x = A_x
    g = _sigmoid((x * gate_w).sum(-1, keepdims=True))
    a = _A_ref(x, A_wqkv, A_wo)
    b = _B_ref(x, B_w1, B_b1, B_w2, B_b2)
    return g * a + (1 - g) * b
```

```cpp
#include <cuda_runtime.h>
#include <cuda_bf16.h>
#include <cuda.h>
#include <stdint.h>

namespace {

constexpr int S_ = 2048, D_ = 640, F_ = 1536;
constexpr int NQ = 10, NG = 16, NPO = 5, NPY = 12;
constexpr int KB = 1024;
constexpr int X_OFF = 160 * KB;
constexpr int HALO_OFF = X_OFF;
constexpr int OST_OFF = X_OFF + 26 * KB;
constexpr int RECVG_OFF = X_OFF;
constexpr int UST_OFF = X_OFF + 48 * KB;
constexpr int RECVP_OFF = X_OFF;
constexpr int OUTST_OFF = X_OFF + 40 * KB;
constexpr int BAR_OFF = 225 * KB;
constexpr int SMEM_BYTES = 226 * KB;
constexpr int B_FULL = 0, B_EMPTY = 8, B_HALO = 16, B_XFREE1 = 17, B_RECVG = 18, B_XFREE2 = 19, B_RECVP = 20;
constexpr int STAGGER = 800;

struct Maps { CUtensorMap x, wqm, wqr, h, w1, old_, wo, w2, uld, ost, ust, out; };
struct Ptrs { const __nv_bfloat16 *x, *b1, *b2, *gw; int smid_mode; };

__device__ __align__(1024) __nv_bfloat16 g_h[S_ * D_];
__device__ __align__(1024) __nv_bfloat16 g_o[S_ * D_];
__device__ __align__(1024) __nv_bfloat16 g_u[D_ * F_];
__device__ __align__(128) float2 g_gate[S_];
__device__ __align__(128) uint4 g_halo[128 * 2 * 10 * 32];
__device__ __align__(128) unsigned g_cnt_h[16 * 8];
__device__ __align__(128) unsigned g_cnt_o[32 * 8];
__device__ __align__(128) unsigned g_cnt_u[24 * 8];
__device__ __align__(128) unsigned g_epoch[160 * 8];
#define TS(i)

#define TRAP() break
template <int N, int TA, int TB> struct Wgmma;
template <int TA, int TB> struct Wgmma<48, TA, TB> {
  static __device__ __forceinline__ void run(float (&d)[24], uint64_t da, uint64_t db, int sd) {
    asm volatile("{\n.reg .pred p;\nsetp.ne.b32 p, %26, 0;\n"
      "wgmma.mma_async.sync.aligned.m64n48k16.f32.bf16.bf16 {%0, %1, %2, %3, %4, %5, %6, %7, %8, %9, %10, %11, %12, %13, %14, %15, %16, %17, %18, %19, %20, %21, %22, %23}, %24, %25, p, 1, 1, %27, %28;\n}\n"
      : "+f"(d[0]), "+f"(d[1]), "+f"(d[2]), "+f"(d[3]), "+f"(d[4]), "+f"(d[5]), "+f"(d[6]), "+f"(d[7]), "+f"(d[8]), "+f"(d[9]), "+f"(d[10]), "+f"(d[11]), "+f"(d[12]), "+f"(d[13]), "+f"(d[14]), "+f"(d[15]), "+f"(d[16]), "+f"(d[17]), "+f"(d[18]), "+f"(d[19]), "+f"(d[20]), "+f"(d[21]), "+f"(d[22]), "+f"(d[23])
      : "l"(da), "l"(db), "r"(sd), "n"(TA), "n"(TB));
  }
};
template <int TA, int TB> struct Wgmma<128, TA, TB> {
  static __device__ __forceinline__ void run(float (&d)[64], uint64_t da, uint64_t db, int sd) {
    asm volatile("{\n.reg .pred p;\nsetp.ne.b32 p, %66, 0;\n"
      "wgmma.mma_async.sync.aligned.m64n128k16.f32.bf16.bf16 {%0, %1, %2, %3, %4, %5, %6, %7, %8, %9, %10, %11, %12, %13, %14, %15, %16, %17, %18, %19, %20, %21, %22, %23, %24, %25, %26, %27, %28, %29, %30, %31, %32, %33, %34, %35, %36, %37, %38, %39, %40, %41, %42, %43, %44, %45, %46, %47, %48, %49, %50, %51, %52, %53, %54, %55, %56, %57, %58, %59, %60, %61, %62, %63}, %64, %65, p, 1, 1, %67, %68;\n}\n"
      : "+f"(d[0]), "+f"(d[1]), "+f"(d[2]), "+f"(d[3]), "+f"(d[4]), "+f"(d[5]), "+f"(d[6]), "+f"(d[7]), "+f"(d[8]), "+f"(d[9]), "+f"(d[10]), "+f"(d[11]), "+f"(d[12]), "+f"(d[13]), "+f"(d[14]), "+f"(d[15]), "+f"(d[16]), "+f"(d[17]), "+f"(d[18]), "+f"(d[19]), "+f"(d[20]), "+f"(d[21]), "+f"(d[22]), "+f"(d[23]), "+f"(d[24]), "+f"(d[25]), "+f"(d[26]), "+f"(d[27]), "+f"(d[28]), "+f"(d[29]), "+f"(d[30]), "+f"(d[31]), "+f"(d[32]), "+f"(d[33]), "+f"(d[34]), "+f"(d[35]), "+f"(d[36]), "+f"(d[37]), "+f"(d[38]), "+f"(d[39]), "+f"(d[40]), "+f"(d[41]), "+f"(d[42]), "+f"(d[43]), "+f"(d[44]), "+f"(d[45]), "+f"(d[46]), "+f"(d[47]), "+f"(d[48]), "+f"(d[49]), "+f"(d[50]), "+f"(d[51]), "+f"(d[52]), "+f"(d[53]), "+f"(d[54]), "+f"(d[55]), "+f"(d[56]), "+f"(d[57]), "+f"(d[58]), "+f"(d[59]), "+f"(d[60]), "+f"(d[61]), "+f"(d[62]), "+f"(d[63])
      : "l"(da), "l"(db), "r"(sd), "n"(TA), "n"(TB));
  }
};
template <int TA, int TB> struct Wgmma<160, TA, TB> {
  static __device__ __forceinline__ void run(float (&d)[80], uint64_t da, uint64_t db, int sd) {
    asm volatile("{\n.reg .pred p;\nsetp.ne.b32 p, %82, 0;\n"
      "wgmma.mma_async.sync.aligned.m64n160k16.f32.bf16.bf16 {%0, %1, %2, %3, %4, %5, %6, %7, %8, %9, %10, %11, %12, %13, %14, %15, %16, %17, %18, %19, %20, %21, %22, %23, %24, %25, %26, %27, %28, %29, %30, %31, %32, %33, %34, %35, %36, %37, %38, %39, %40, %41, %42, %43, %44, %45, %46, %47, %48, %49, %50, %51, %52, %53, %54, %55, %56, %57, %58, %59, %60, %61, %62, %63, %64, %65, %66, %67, %68, %69, %70, %71, %72, %73, %74, %75, %76, %77, %78, %79}, %80, %81, p, 1, 1, %83, %84;\n}\n"
      : "+f"(d[0]), "+f"(d[1]), "+f"(d[2]), "+f"(d[3]), "+f"(d[4]), "+f"(d[5]), "+f"(d[6]), "+f"(d[7]), "+f"(d[8]), "+f"(d[9]), "+f"(d[10]), "+f"(d[11]), "+f"(d[12]), "+f"(d[13]), "+f"(d[14]), "+f"(d[15]), "+f"(d[16]), "+f"(d[17]), "+f"(d[18]), "+f"(d[19]), "+f"(d[20]), "+f"(d[21]), "+f"(d[22]), "+f"(d[23]), "+f"(d[24]), "+f"(d[25]), "+f"(d[26]), "+f"(d[27]), "+f"(d[28]), "+f"(d[29]), "+f"(d[30]), "+f"(d[31]), "+f"(d[32]), "+f"(d[33]), "+f"(d[34]), "+f"(d[35]), "+f"(d[36]), "+f"(d[37]), "+f"(d[38]), "+f"(d[39]), "+f"(d[40]), "+f"(d[41]), "+f"(d[42]), "+f"(d[43]), "+f"(d[44]), "+f"(d[45]), "+f"(d[46]), "+f"(d[47]), "+f"(d[48]), "+f"(d[49]), "+f"(d[50]), "+f"(d[51]), "+f"(d[52]), "+f"(d[53]), "+f"(d[54]), "+f"(d[55]), "+f"(d[56]), "+f"(d[57]), "+f"(d[58]), "+f"(d[59]), "+f"(d[60]), "+f"(d[61]), "+f"(d[62]), "+f"(d[63]), "+f"(d[64]), "+f"(d[65]), "+f"(d[66]), "+f"(d[67]), "+f"(d[68]), "+f"(d[69]), "+f"(d[70]), "+f"(d[71]), "+f"(d[72]), "+f"(d[73]), "+f"(d[74]), "+f"(d[75]), "+f"(d[76]), "+f"(d[77]), "+f"(d[78]), "+f"(d[79])
      : "l"(da), "l"(db), "r"(sd), "n"(TA), "n"(TB));
  }
};
template <int TA, int TB> struct Wgmma<192, TA, TB> {
  static __device__ __forceinline__ void run(float (&d)[96], uint64_t da, uint64_t db, int sd) {
    asm volatile("{\n.reg .pred p;\nsetp.ne.b32 p, %98, 0;\n"
      "wgmma.mma_async.sync.aligned.m64n192k16.f32.bf16.bf16 {%0, %1, %2, %3, %4, %5, %6, %7, %8, %9, %10, %11, %12, %13, %14, %15, %16, %17, %18, %19, %20, %21, %22, %23, %24, %25, %26, %27, %28, %29, %30, %31, %32, %33, %34, %35, %36, %37, %38, %39, %40, %41, %42, %43, %44, %45, %46, %47, %48, %49, %50, %51, %52, %53, %54, %55, %56, %57, %58, %59, %60, %61, %62, %63, %64, %65, %66, %67, %68, %69, %70, %71, %72, %73, %74, %75, %76, %77, %78, %79, %80, %81, %82, %83, %84, %85, %86, %87, %88, %89, %90, %91, %92, %93, %94, %95}, %96, %97, p, 1, 1, %99, %100;\n}\n"
      : "+f"(d[0]), "+f"(d[1]), "+f"(d[2]), "+f"(d[3]), "+f"(d[4]), "+f"(d[5]), "+f"(d[6]), "+f"(d[7]), "+f"(d[8]), "+f"(d[9]), "+f"(d[10]), "+f"(d[11]), "+f"(d[12]), "+f"(d[13]), "+f"(d[14]), "+f"(d[15]), "+f"(d[16]), "+f"(d[17]), "+f"(d[18]), "+f"(d[19]), "+f"(d[20]), "+f"(d[21]), "+f"(d[22]), "+f"(d[23]), "+f"(d[24]), "+f"(d[25]), "+f"(d[26]), "+f"(d[27]), "+f"(d[28]), "+f"(d[29]), "+f"(d[30]), "+f"(d[31]), "+f"(d[32]), "+f"(d[33]), "+f"(d[34]), "+f"(d[35]), "+f"(d[36]), "+f"(d[37]), "+f"(d[38]), "+f"(d[39]), "+f"(d[40]), "+f"(d[41]), "+f"(d[42]), "+f"(d[43]), "+f"(d[44]), "+f"(d[45]), "+f"(d[46]), "+f"(d[47]), "+f"(d[48]), "+f"(d[49]), "+f"(d[50]), "+f"(d[51]), "+f"(d[52]), "+f"(d[53]), "+f"(d[54]), "+f"(d[55]), "+f"(d[56]), "+f"(d[57]), "+f"(d[58]), "+f"(d[59]), "+f"(d[60]), "+f"(d[61]), "+f"(d[62]), "+f"(d[63]), "+f"(d[64]), "+f"(d[65]), "+f"(d[66]), "+f"(d[67]), "+f"(d[68]), "+f"(d[69]), "+f"(d[70]), "+f"(d[71]), "+f"(d[72]), "+f"(d[73]), "+f"(d[74]), "+f"(d[75]), "+f"(d[76]), "+f"(d[77]), "+f"(d[78]), "+f"(d[79]), "+f"(d[80]), "+f"(d[81]), "+f"(d[82]), "+f"(d[83]), "+f"(d[84]), "+f"(d[85]), "+f"(d[86]), "+f"(d[87]), "+f"(d[88]), "+f"(d[89]), "+f"(d[90]), "+f"(d[91]), "+f"(d[92]), "+f"(d[93]), "+f"(d[94]), "+f"(d[95])
      : "l"(da), "l"(db), "r"(sd), "n"(TA), "n"(TB));
  }
};

__device__ __forceinline__ uint32_t smem_u32(const void* p) { return (uint32_t)__cvta_generic_to_shared(p); }
__device__ __forceinline__ void mbar_init(uint32_t bar, int cnt) { asm volatile("mbarrier.init.shared::cta.b64 [%0], %1;" ::"r"(bar), "r"(cnt) : "memory"); }
__device__ __forceinline__ void mbar_expect_tx(uint32_t bar, uint32_t bytes) { asm volatile("mbarrier.arrive.expect_tx.shared::cta.b64 _, [%0], %1;" ::"r"(bar), "r"(bytes) : "memory"); }
__device__ __forceinline__ void mbar_arrive(uint32_t bar) { asm volatile("mbarrier.arrive.shared::cta.b64 _, [%0];" ::"r"(bar) : "memory"); }
__device__ __forceinline__ void mbar_arrive2(uint32_t bar) { asm volatile("mbarrier.arrive.shared::cta.b64 _, [%0], 2;" ::"r"(bar) : "memory"); }
__device__ __forceinline__ uint32_t mapa(uint32_t a, uint32_t cta) { uint32_t r; asm("mapa.shared::cluster.u32 %0, %1, %2;" : "=r"(r) : "r"(a), "r"(cta)); return r; }
__device__ __forceinline__ void mbar_arrive_remote(uint32_t rbar) { asm volatile("mbarrier.arrive.shared::cluster.b64 _, [%0];" ::"r"(rbar) : "memory"); }
__device__ __forceinline__ bool mbar_try(uint32_t bar, uint32_t parity) {
  uint32_t ok;
  asm volatile("{\n.reg .pred p;\nmbarrier.try_wait.parity.shared::cta.b64 p, [%1], %2;\nselp.b32 %0, 1, 0, p;\n}" : "=r"(ok) : "r"(bar), "r"(parity) : "memory");
  return ok;
}
__device__ __forceinline__ void mbar_wait(uint32_t bar, uint32_t parity) {
  if (mbar_try(bar, parity)) return;
  int n = 0;
  while (!mbar_try(bar, parity)) { if (++n > (1 << 18)) TRAP(); }
}
__device__ __forceinline__ void tma2d(uint32_t dst, const CUtensorMap* m, int c0, int c1, uint32_t bar) {
  asm volatile("cp.async.bulk.tensor.2d.shared::cluster.global.mbarrier::complete_tx::bytes [%0], [%1, {%3,%4}], [%2];" ::"r"(dst), "l"(m), "r"(bar), "r"(c0), "r"(c1) : "memory");
}
__device__ __forceinline__ void tma3d(uint32_t dst, const CUtensorMap* m, int c0, int c1, int c2, uint32_t bar) {
  asm volatile("cp.async.bulk.tensor.3d.shared::cluster.global.mbarrier::complete_tx::bytes [%0], [%1, {%3,%4,%5}], [%2];" ::"r"(dst), "l"(m), "r"(bar), "r"(c0), "r"(c1), "r"(c2) : "memory");
}
__device__ __forceinline__ void tma3d_mc(uint32_t dst, const CUtensorMap* m, int c0, int c1, int c2, uint32_t bar) {
  asm volatile("cp.async.bulk.tensor.3d.shared::cluster.global.mbarrier::complete_tx::bytes.multicast::cluster [%0], [%1, {%3,%4,%5}], [%2], %6;" ::"r"(dst), "l"(m), "r"(bar), "r"(c0), "r"(c1), "r"(c2), "h"((uint16_t)3) : "memory");
}
__device__ __forceinline__ void tma2d_st(const CUtensorMap* m, int c0, int c1, uint32_t src) {
  asm volatile("cp.async.bulk.tensor.2d.global.shared::cta.bulk_group [%0, {%2,%3}], [%1];" ::"l"(m), "r"(src), "r"(c0), "r"(c1) : "memory");
}
__device__ __forceinline__ void tma3d_st(const CUtensorMap* m, int c0, int c1, int c2, uint32_t src) {
  asm volatile("cp.async.bulk.tensor.3d.global.shared::cta.bulk_group [%0, {%2,%3,%4}], [%1];" ::"l"(m), "r"(src), "r"(c0), "r"(c1), "r"(c2) : "memory");
}
__device__ __forceinline__ void bulk_commit() { asm volatile("cp.async.bulk.commit_group;" ::: "memory"); }
__device__ __forceinline__ void bulk_wait0() { asm volatile("cp.async.bulk.wait_group 0;" ::: "memory"); }
__device__ __forceinline__ void bulk_wait0_read() { asm volatile("cp.async.bulk.wait_group.read 0;" ::: "memory"); }
__device__ __forceinline__ void fence_async_smem() { asm volatile("fence.proxy.async.shared::cta;" ::: "memory"); }
__device__ __forceinline__ void fence_async_all() { asm volatile("fence.proxy.async;" ::: "memory"); }
__device__ __forceinline__ void wg_fence() { asm volatile("wgmma.fence.sync.aligned;" ::: "memory"); }
__device__ __forceinline__ void wg_commit() { asm volatile("wgmma.commit_group.sync.aligned;" ::: "memory"); }
template <int N> __device__ __forceinline__ void wg_wait() { asm volatile("wgmma.wait_group.sync.aligned %0;" ::"n"(N) : "memory"); }
template <int N> __device__ __forceinline__ void reg_fence(float (&a)[N]) {
#pragma unroll
  for (int i = 0; i < N; i++) asm volatile("" : "+f"(a[i])::"memory");
}
template <int ID, int N> __device__ __forceinline__ void bar_sync() { asm volatile("bar.sync %0, %1;" ::"n"(ID), "n"(N) : "memory"); }
template <int ID, int N> __device__ __forceinline__ void bar_arrive() { asm volatile("bar.arrive %0, %1;" ::"n"(ID), "n"(N) : "memory"); }
__device__ __forceinline__ uint64_t mkdesc(uint32_t addr, uint32_t lbo, uint32_t sbo, uint32_t swz) {
  return (uint64_t)((addr & 0x3FFFF) >> 4) | ((uint64_t)(lbo >> 4) << 16) | ((uint64_t)(sbo >> 4) << 32) | ((uint64_t)swz << 62);
}
__device__ __forceinline__ uint32_t pack2(float lo, float hi) { uint32_t r; asm("cvt.rn.bf16x2.f32 %0, %1, %2;" : "=r"(r) : "f"(hi), "f"(lo)); return r; }
__device__ __forceinline__ float bf_lo(uint32_t v) { return __uint_as_float(v << 16); }
__device__ __forceinline__ float bf_hi(uint32_t v) { return __uint_as_float(v & 0xFFFF0000u); }
__device__ __forceinline__ float bf_round(float v) { return __bfloat162float(__float2bfloat16_rn(v)); }
__device__ __forceinline__ uint32_t movm(uint32_t a) { uint32_t d; asm volatile("movmatrix.sync.aligned.m8n8.trans.b16 %0, %1;" : "=r"(d) : "r"(a)); return d; }
__device__ __forceinline__ void stsm4(uint32_t addr, uint32_t a, uint32_t b, uint32_t c, uint32_t d) {
  asm volatile("stmatrix.sync.aligned.m8n8.x4.shared.b16 [%0], {%1,%2,%3,%4};" ::"r"(addr), "r"(a), "r"(b), "r"(c), "r"(d) : "memory");
}
__device__ __forceinline__ void stsm2(uint32_t addr, uint32_t a, uint32_t b) {
  asm volatile("stmatrix.sync.aligned.m8n8.x2.shared.b16 [%0], {%1,%2};" ::"r"(addr), "r"(a), "r"(b) : "memory");
}
__device__ __forceinline__ void sts64(uint32_t addr, uint32_t a, uint32_t b) { asm volatile("st.shared.v2.b32 [%0], {%1,%2};" ::"r"(addr), "r"(a), "r"(b) : "memory"); }
__device__ __forceinline__ void lds64(uint32_t addr, uint32_t& a, uint32_t& b) { asm volatile("ld.shared.v2.b32 {%0,%1}, [%2];" : "=r"(a), "=r"(b) : "r"(addr) : "memory"); }
__device__ __forceinline__ float4 lds128f(uint32_t addr) { float4 v; asm volatile("ld.shared.v4.f32 {%0,%1,%2,%3}, [%4];" : "=f"(v.x), "=f"(v.y), "=f"(v.z), "=f"(v.w) : "r"(addr) : "memory"); return v; }
__device__ __forceinline__ void st_async4(uint32_t raddr, float a, float b, float c, float d, uint32_t rbar) {
  asm volatile("st.async.weak.shared::cluster.mbarrier::complete_tx::bytes.v4.f32 [%0], {%1,%2,%3,%4}, [%5];" ::"r"(raddr), "f"(a), "f"(b), "f"(c), "f"(d), "r"(rbar) : "memory");
}
__device__ __forceinline__ void mma16816(float (&c)[4], uint32_t a0, uint32_t a1, uint32_t a2, uint32_t a3, uint32_t b0, uint32_t b1) {
  asm volatile("mma.sync.aligned.m16n8k16.row.col.f32.bf16.bf16.f32 {%0,%1,%2,%3}, {%4,%5,%6,%7}, {%8,%9}, {%0,%1,%2,%3};"
               : "+f"(c[0]), "+f"(c[1]), "+f"(c[2]), "+f"(c[3]) : "r"(a0), "r"(a1), "r"(a2), "r"(a3), "r"(b0), "r"(b1));
}
__device__ __forceinline__ void mma1688z(float (&c)[4], uint32_t a0, uint32_t a1, uint32_t b0) {
  asm volatile("mma.sync.aligned.m16n8k8.row.col.f32.bf16.bf16.f32 {%0,%1,%2,%3}, {%4,%5}, {%6}, {%7,%7,%7,%7};"
               : "=f"(c[0]), "=f"(c[1]), "=f"(c[2]), "=f"(c[3]) : "r"(a0), "r"(a1), "r"(b0), "f"(0.f));
}
__device__ __forceinline__ unsigned ld_acquire(const unsigned* p) { unsigned v; asm volatile("ld.acquire.gpu.global.u32 %0, [%1];" : "=r"(v) : "l"(p) : "memory"); return v; }
__device__ __forceinline__ unsigned ld_relaxed(const unsigned* p) { unsigned v; asm volatile("ld.relaxed.gpu.global.u32 %0, [%1];" : "=r"(v) : "l"(p) : "memory"); return v; }
__device__ __forceinline__ void red_release(unsigned* p) { asm volatile("red.release.gpu.global.add.u32 [%0], 1;" ::"l"(p) : "memory"); }
__device__ __forceinline__ void wait_counters(const unsigned* p, unsigned target, bool active) {
  int n = 0;
  while (true) {
    unsigned v = active ? ld_acquire(p) : target;
    if (__all_sync(0xffffffffu, (int)(v - target) >= 0)) break;
    if (++n > (1 << 16)) TRAP();
  }
  fence_async_all();
}
__device__ __forceinline__ float ex2(float x) { float y; asm("ex2.approx.ftz.f32 %0, %1;" : "=f"(y) : "f"(x)); return y; }
__device__ __forceinline__ float gelu_tanh(float x) {
  float z = x * fmaf(x * x, 0.044715f * 0.7978845608028654f, 0.7978845608028654f), t;
  asm("tanh.approx.f32 %0, %1;" : "=f"(t) : "f"(z));
  float hx = 0.5f * x;
  return fmaf(hx, t, hx);
}

__device__ __forceinline__ int q_off(int i) { int s = i & 3; return s == 3 ? X_OFF : s * 48 * KB; }
__device__ __forceinline__ int g_off(int n) { return ((n + 3) % 5) * 32 * KB; }
__device__ __forceinline__ int pA_off(int n) { return (n & 3) * 36 * KB; }
__device__ __forceinline__ int pB_off(int n) { int s = n & 3; return s == 0 ? 128 * KB : s * 36 * KB - 20 * KB; }

__device__ __forceinline__ void win_softmax(const float (&S)[3][4], bool e0, bool e1, bool first, uint32_t maskE,
                                            uint32_t& pe, uint32_t& pl, uint32_t& he, uint32_t& hl) {
  const float sc = 0.22360679774997896f;
  float l0 = (e0 ? S[0][0] : S[1][0]) * sc, l1 = (e1 ? S[0][1] : S[1][1]) * sc;
  float l2 = (e0 ? S[1][2] : S[2][2]) * sc, l3 = (e1 ? S[1][3] : S[2][3]) * sc;
  if (first) { if (e0) l0 = -1e9f; if (e1) l1 = -1e9f; }
  float m0 = fmaxf(l0, l1), m1 = fmaxf(l2, l3);
  m0 = fmaxf(m0, __shfl_xor_sync(0xffffffffu, m0, 1)); m1 = fmaxf(m1, __shfl_xor_sync(0xffffffffu, m1, 1));
  m0 = fmaxf(m0, __shfl_xor_sync(0xffffffffu, m0, 2)); m1 = fmaxf(m1, __shfl_xor_sync(0xffffffffu, m1, 2));
  const float L2E = 1.4426950408889634f;
  float p0 = ex2((l0 - m0) * L2E), p1 = ex2((l1 - m0) * L2E), p2 = ex2((l2 - m1) * L2E), p3 = ex2((l3 - m1) * L2E);
  float s0 = p0 + p1, s1 = p2 + p3;
  s0 += __shfl_xor_sync(0xffffffffu, s0, 1); s1 += __shfl_xor_sync(0xffffffffu, s1, 1);
  s0 += __shfl_xor_sync(0xffffffffu, s0, 2); s1 += __shfl_xor_sync(0xffffffffu, s1, 2);
  float r0 = __fdividef(1.f, s0), r1 = __fdividef(1.f, s1);
  uint32_t P0 = pack2(p0 * r0, p1 * r0), P1 = pack2(p2 * r1, p3 * r1);
  pe = P0 & maskE; pl = P0 & ~maskE; he = P1 & maskE; hl = P1 & ~maskE;
}

__global__ void __cluster_dims__(2, 1, 1) __launch_bounds__(384, 1)
fused_kernel(const __grid_constant__ Maps mp, const Ptrs pt) {
  extern __shared__ __align__(1024) uint8_t smem_raw[];
  const uint32_t base = smem_u32(smem_raw);
  const uint32_t bars = base + BAR_OFF;
  const int tid = threadIdx.x, lane = tid & 31;
  const int warp = __shfl_sync(0xffffffffu, tid >> 5, 0);
  uint32_t r; asm("mov.u32 %0, %%cluster_ctarank;" : "=r"(r));
  auto BAR = [&](int i) { return bars + i * 8; };
  auto FULL = [&](int s) { return bars + (B_FULL + (s & 7)) * 8; };
  auto EMPTY = [&](int s) { return bars + (B_EMPTY + (s & 7)) * 8; };
  auto PAR = [&](int s) { return (uint32_t)((s >> 3) & 1); };

  if (lane == 0) {
    if (warp < 8) { mbar_init(BAR(B_FULL + warp), 1); mbar_init(BAR(B_EMPTY + warp), 4); }
    else if (warp == 9) { mbar_init(BAR(B_HALO), 2); mbar_init(BAR(B_XFREE1), 2); }
    else if (warp == 10) { mbar_init(BAR(B_RECVG), 1); mbar_expect_tx(BAR(B_RECVG), 32 * KB); mbar_init(BAR(B_XFREE2), 2); }
    else if (warp == 11) { mbar_init(BAR(B_RECVP), 1); mbar_expect_tx(BAR(B_RECVP), 40 * KB); }
    else {
      asm volatile("prefetch.tensormap [%0];" ::"l"(&mp.x) : "memory");
      asm volatile("prefetch.tensormap [%0];" ::"l"(&mp.wqm) : "memory");
      asm volatile("prefetch.tensormap [%0];" ::"l"(&mp.wqr) : "memory");
    }
    asm volatile("fence.mbarrier_init.release.cluster;" ::: "memory");
  }
  __syncwarp();
  asm volatile("barrier.cluster.arrive.relaxed.aligned;" ::: "memory");

  int t;
  if (pt.smid_mode) { unsigned smid; asm("mov.u32 %0, %%smid;" : "=r"(smid)); t = smid >> 1; }
  else { t = blockIdx.x >> 1; t = t < 4 ? t + 62 : t - 4; }
  int g, i;
  if (t < 32) { g = t & 7; i = t >> 3; }
  else if (t < 60) { int u = t - 32; int q7 = (u * 37) >> 8; g = 1 + u - 7 * q7; i = 4 + q7; }
  else { g = 0; i = t - 58; }
  const bool idle = (t == 60 || t == 61);
  const int eslot = (t * 2 + r) * 8;
  const int qm = g * 2 + r, qj = i;
  int gd, gf; bool hasG;
  { int n = (g & 1) ? 7 : 8; hasG = i < n; int tt = (g >> 1) * 15 + (g & 1) * 8 + (hasG ? i : 6); gf = (tt * 52) >> 8; gd = tt - gf * 5; }
  const int pm = g * 2 + (i >> 2), pn = i & 3;

  asm volatile("barrier.cluster.wait.aligned;" ::: "memory");

  if (warp >= 8) {
    asm volatile("setmaxnreg.dec.sync.aligned.u32 104;");
    if (idle) {
      if (warp == 8) {
        unsigned ep = ld_relaxed(&g_epoch[eslot]) + 1;
        wait_counters(&g_cnt_h[(lane & 15) * 8], ep * 8, true);
        if (lane == 0) g_epoch[eslot] = ep;
      }
    } else if (warp == 8) {
      TS(0);
      unsigned ep = 0;
      long long t0 = clock64();
#pragma unroll 1
      for (int s = 0; s < NQ; s++) {
        if (s >= 4) mbar_wait(EMPTY(s - 4), PAR(s - 4));
        else { while (clock64() - t0 < s * STAGGER) {} }
        if (lane == 0) {
          mbar_expect_tx(FULL(s), 46 * KB);
          uint32_t a = base + q_off(s), b = a + 16 * KB + r * 16 * KB;
          tma3d(a, &mp.x, s * 64, qm * 64, 0, FULL(s));
          tma3d_mc(b, &mp.wqm, qj * 80, s * 64 + r * 32, 0, FULL(s));
          tma3d_mc(b + 12 * KB, &mp.wqr, qj * 80 + 64, s * 64 + r * 32, 0, FULL(s));
        }
        __syncwarp();
        if (s == 0) { TS(1); ep = ld_relaxed(&g_epoch[eslot]) + 1; }
        if (s == 8) { wait_counters(&g_cnt_h[(lane & 15) * 8], ep * 8, true); TS(2); }
      }
#pragma unroll 1
      for (int n = 0; n < NG; n++) {
        int dep = n < 2 ? 6 : n == 2 ? 8 : n < 5 ? 9 : NQ + n - 5;
        mbar_wait(EMPTY(dep), PAR(dep));
        if (lane == 0) {
          int s = NQ + n;
          mbar_expect_tx(FULL(s), 32 * KB);
          uint32_t a = base + g_off(n);
          tma3d(a, &mp.h, 0, r * 1024 + n * 64, gd * 2, FULL(s));
          tma3d(a + 16 * KB, &mp.w1, 0, r * 1024 + n * 64, gf * 2, FULL(s));
        }
        __syncwarp();
      }
      TS(3);
      wait_counters(&g_cnt_o[(pm * 2 + r) * 8], ep * 4, lane == 0);
      TS(4);
#pragma unroll 1
      for (int n = 0; n < NPO + NPY; n++) {
        int dep = n < 4 ? NQ + 12 + n : NQ + NG + n - 4;
        int s = NQ + NG + n;
        mbar_wait(EMPTY(dep), PAR(dep));
        if (n < NPO) {
          if (lane == 0) {
            mbar_expect_tx(FULL(s), 36 * KB);
            tma2d(base + pA_off(n), &mp.old_, r * 320 + n * 64, pm * 128, FULL(s));
            tma3d(base + pB_off(n), &mp.wo, 0, r * 320 + n * 64, pn * 5, FULL(s));
          }
        } else {
          int k = r * 768 + (n - NPO) * 64;
          if (lane == 0) {
            mbar_expect_tx(FULL(s), 36 * KB);
            tma3d(base + pA_off(n), &mp.w2, 0, k, pm * 2, FULL(s));
          }
          if (n == NPO) { TS(5); wait_counters(&g_cnt_u[(r * 12 + (lane < 12 ? lane : 0)) * 8], ep * 5, true); TS(6); }
          if (lane == 0) tma2d(base + pB_off(n), &mp.uld, k, pn * 160, FULL(s));
        }
        __syncwarp();
      }
      if (lane == 0) g_epoch[eslot] = ep;
    } else {
      const int hw = warp - 9;
      const unsigned ep = ld_relaxed(&g_epoch[eslot]) + 1;
      {
        uint2 gwv[5];
#pragma unroll
        for (int c = 0; c < 5; c++) gwv[c] = __ldg((const uint2*)pt.gw + c * 32 + lane);
#pragma unroll 1
        for (int bt = 0; bt < 2; bt++) {
          uint2 xv[3][5];
          const int row0 = qm * 128 + qj * 16;
#pragma unroll
          for (int k = 0; k < 3; k++) {
            int lr = min(hw + (bt * 3 + k) * 3, 15);
#pragma unroll
            for (int c = 0; c < 5; c++) xv[k][c] = __ldg((const uint2*)(pt.x + (size_t)(row0 + lr) * D_) + c * 32 + lane);
          }
#pragma unroll
          for (int k = 0; k < 3; k++) {
            int lr = hw + (bt * 3 + k) * 3;
            float sum = 0.f, z = 0.f;
#pragma unroll
            for (int c = 0; c < 5; c++) {
              float a0 = bf_lo(xv[k][c].x), a1 = bf_hi(xv[k][c].x), a2 = bf_lo(xv[k][c].y), a3 = bf_hi(xv[k][c].y);
              sum += (a0 + a1) + (a2 + a3);
              uint32_t p0 = pack2(a0 * bf_lo(gwv[c].x), a1 * bf_hi(gwv[c].x)), p1 = pack2(a2 * bf_lo(gwv[c].y), a3 * bf_hi(gwv[c].y));
              z += (bf_lo(p0) + bf_hi(p0)) + (bf_lo(p1) + bf_hi(p1));
            }
#pragma unroll
            for (int o = 16; o > 0; o >>= 1) { sum += __shfl_xor_sync(0xffffffffu, sum, o); z += __shfl_xor_sync(0xffffffffu, z, o); }
            float mean = sum * (1.f / D_), var = 0.f;
#pragma unroll
            for (int c = 0; c < 5; c++) {
              float a0 = bf_lo(xv[k][c].x) - mean, a1 = bf_hi(xv[k][c].x) - mean, a2 = bf_lo(xv[k][c].y) - mean, a3 = bf_hi(xv[k][c].y) - mean;
              var += (a0 * a0 + a1 * a1) + (a2 * a2 + a3 * a3);
            }
#pragma unroll
            for (int o = 16; o > 0; o >>= 1) var += __shfl_xor_sync(0xffffffffu, var, o);
            float mb = bf_round(mean);
            float sd = bf_round(sqrtf(bf_round(bf_round(var * (1.f / D_)) + 1e-5f)));
            float rs = 1.f / sd;
            if (lr < 16) {
#pragma unroll
              for (int c = 0; c < 5; c++) {
                uint32_t d0 = pack2(bf_lo(xv[k][c].x) - mb, bf_hi(xv[k][c].x) - mb), d1 = pack2(bf_lo(xv[k][c].y) - mb, bf_hi(xv[k][c].y) - mb);
                uint2 o; o.x = pack2(bf_lo(d0) * rs, bf_hi(d0) * rs); o.y = pack2(bf_lo(d1) * rs, bf_hi(d1) * rs);
                *((uint2*)(g_h + (size_t)(row0 + lr) * D_) + c * 32 + lane) = o;
              }
              if (lane == 0) {
                float gg = bf_round(1.f / (1.f + __expf(-bf_round(z))));
                g_gate[row0 + lr] = make_float2(gg, bf_round(1.f - gg));
              }
            }
          }
        }
        fence_async_all();
        bar_sync<1, 96>();
        if (hw == 0 && lane == 0) red_release(&g_cnt_h[qm * 8]);
        if (hw == 0) TS(8);
      }
      if (hw < 2) {
        mbar_wait(EMPTY(7), 0);
        uint32_t dst = base + HALO_OFF + hw * 5 * 2560 + lane * 8;
        if (qm == 0) {
#pragma unroll
          for (int c = 0; c < 10; c++) sts64(dst + c * 256, 0, 0);
        } else {
          mbar_wait(EMPTY(9), 1);
          const uint4* src = g_halo + (((qm - 1) * 8 + qj) * 2 + hw) * 320 + lane;
          uint4 v[10];
          int n = 0;
          while (true) {
            bool ok = true;
#pragma unroll
            for (int c = 0; c < 10; c++) {
              asm volatile("ld.relaxed.gpu.global.v4.u32 {%0,%1,%2,%3}, [%4];" : "=r"(v[c].x), "=r"(v[c].y), "=r"(v[c].z), "=r"(v[c].w) : "l"(src + c * 32) : "memory");
            }
#pragma unroll
            for (int c = 0; c < 10; c++) ok = ok && v[c].y == ep && v[c].w == ep;
            if (__all_sync(0xffffffffu, ok)) break;
            if (++n > (1 << 16)) TRAP();
          }
#pragma unroll
          for (int c = 0; c < 10; c++) sts64(dst + c * 256, v[c].x, v[c].z);
        }
        __syncwarp();
        if (lane == 0) mbar_arrive(BAR(B_HALO));
        if (hw == 0) TS(9);
      } else {
        bar_sync<2, 288>();
        if (lane == 0) {
          tma3d_st(&mp.ost, qj * 80, qm * 64, 0, base + OST_OFF);
          bulk_commit(); bulk_wait0();
          red_release(&g_cnt_o[(qm * 2 + (qj >> 2)) * 8]);
          mbar_arrive(BAR(B_XFREE1)); mbar_arrive_remote(mapa(BAR(B_XFREE1), r ^ 1));
        }
        TS(10);
        __syncwarp();
        bar_sync<3, 288>();
        TS(11);
        if (lane == 0) {
          if (hasG) {
            tma2d_st(&mp.ust, gf * 128 + r * 64, gd * 128, base + UST_OFF);
            bulk_commit(); bulk_wait0();
            TS(12);
            red_release(&g_cnt_u[(gf * 2 + r) * 8]);
          }
          mbar_arrive(BAR(B_XFREE2)); mbar_arrive_remote(mapa(BAR(B_XFREE2), r ^ 1));
        }
        TS(13);
      }
    }
  } else {
    asm volatile("setmaxnreg.inc.sync.aligned.u32 200;");
    if (!idle) {
    const int wg = warp >> 2, w = warp & 3;
    const bool lead = (tid & 127) == 0;
    const int rho = lane >> 2, q = lane & 3;
    unsigned ep = 0;
    if (w == 3) ep = ld_relaxed(&g_epoch[eslot]) + 1;
    uint32_t Qp[10][2], Kp[10][2], Vt[10][2];
    {
      float acc[96], acr[24];
      const uint32_t rempty = mapa(bars + B_EMPTY * 8, r ^ 1);
#pragma unroll 1
      for (int s = 0; s < NQ; s++) {
        mbar_wait(FULL(s), PAR(s));
        if (s == 0) TS(16 + wg * 16);
        uint32_t a = base + q_off(s) + wg * 8 * KB, b = base + q_off(s) + 16 * KB;
        wg_fence();
#pragma unroll
        for (int k = 0; k < 4; k++) {
          Wgmma<192, 0, 1>::run(acc, mkdesc(a + k * 32, 16, 1024, 1), mkdesc(b + (k >> 1) * 16 * KB + (k & 1) * 2048, 4096, 1024, 1), (s | k) != 0);
          Wgmma<48, 0, 1>::run(acr, mkdesc(a + k * 32, 16, 1024, 1), mkdesc(b + (k >> 1) * 16 * KB + 12 * KB + (k & 1) * 512, 1024, 256, 3), (s | k) != 0);
        }
        wg_commit();
        wg_wait<1>();
        if (s > 0 && lead) { mbar_arrive(EMPTY(s - 1)); mbar_arrive_remote(rempty + ((s - 1) & 7) * 8); }
      }
      wg_wait<0>();
      reg_fence(acc); reg_fence(acr);
      if (lead) { mbar_arrive(EMPTY(NQ - 1)); mbar_arrive_remote(rempty + ((NQ - 1) & 7) * 8); }
#pragma unroll
      for (int c = 0; c < 10; c++) {
        const float* aq = c < 8 ? acc + 4 * c : acr + 4 * (c - 8);
        const float* ak = c < 8 ? acc + 4 * (8 + c) : acr + 4 * (c - 6);
        const float* av = c < 8 ? acc + 4 * (16 + c) : acr + 4 * (c - 4);
        Qp[c][0] = pack2(aq[0], aq[1]); Qp[c][1] = pack2(aq[2], aq[3]);
        Kp[c][0] = pack2(ak[0], ak[1]); Kp[c][1] = pack2(ak[2], ak[3]);
        Vt[c][0] = pack2(av[0], av[1]); Vt[c][1] = pack2(av[2], av[3]);
      }
    }
    TS(17 + wg * 16);
    float accG[64];
    auto g_issue = [&](int n) {
      mbar_wait(FULL(NQ + n), PAR(NQ + n));
      uint32_t a = base + g_off(n) + wg * 8 * KB, b = base + g_off(n) + 16 * KB;
      wg_fence();
#pragma unroll
      for (int k = 0; k < 4; k++)
        Wgmma<128, 1, 1>::run(accG, mkdesc(a + k * 2048, 8192, 1024, 1), mkdesc(b + k * 2048, 8192, 1024, 1), (n | k) != 0);
      wg_commit();
    };
    auto g_step = [&](int n) {
      g_issue(n);
      wg_wait<1>();
      if (lead) mbar_arrive2(EMPTY(NQ + n - 1));
    };
    g_issue(0);
#pragma unroll
    for (int c = 0; c < 10; c++) { Vt[c][1] = movm(Vt[c][1]); }
    if (w == 3) {
      uint4* dst = g_halo + ((qm * 8 + qj) * 2 + wg) * 320 + lane;
#pragma unroll
      for (int c = 0; c < 10; c++)
        asm volatile("st.relaxed.gpu.global.v4.u32 [%0], {%1,%2,%3,%4};" ::"l"(dst + c * 32), "r"(Kp[c][1]), "r"(ep), "r"(Vt[c][1]), "r"(ep) : "memory");
    } else {
      mbar_wait(EMPTY(7), 0);
      uint32_t dst = base + HALO_OFF + (wg * 5 + w + 1) * 2560 + lane * 8;
#pragma unroll
      for (int c = 0; c < 10; c++) sts64(dst + c * 256, Kp[c][1], Vt[c][1]);
    }
#pragma unroll
    for (int c = 0; c < 10; c++) { Vt[c][0] = movm(Vt[c][0]); }
    g_step(1);
    g_step(2);
    if (wg == 0) bar_sync<4, 128>(); else bar_sync<5, 128>();
    g_step(3);
    TS(18 + wg * 16);
    mbar_wait(BAR(B_HALO), 0);
    {
      const bool e0 = 2 * q > rho, e1 = 2 * q + 1 > rho, first = (qm == 0 && w == 0);
      const uint32_t maskE = (e0 ? 0xFFFFu : 0u) | (e1 ? 0xFFFF0000u : 0u);
      const uint32_t hsrc = base + HALO_OFF + (wg * 5 + w) * 2560 + lane * 8;
      const uint32_t odst = base + OST_OFF + (wg * 64 + w * 16 + (lane & 15)) * 160 + (lane >> 4) * 16;
#pragma unroll
      for (int hp = 0; hp < 2; hp++) {
        const int G = 5 * hp;
        uint32_t K0[5], V0[5];
#pragma unroll
        for (int c = 0; c < 5; c++) lds64(hsrc + (G + c) * 256, K0[c], V0[c]);
        const uint32_t qa0 = q < 2 ? Qp[G + 2][0] : 0u, qa1 = q < 2 ? Qp[G + 2][1] : 0u;
        const uint32_t qb0 = q < 2 ? 0u : Qp[G + 2][0], qb1 = q < 2 ? 0u : Qp[G + 2][1];
        float SA[3][4], SB[3][4];
#pragma unroll
        for (int T = 0; T < 3; T++) {
          auto KF = [&](int c) { return T == 0 ? K0[c] : Kp[G + c][T - 1]; };
          mma1688z(SA[T], qa0, qa1, KF(2));
          mma1688z(SB[T], qb0, qb1, KF(2));
          mma16816(SA[T], Qp[G][0], Qp[G][1], Qp[G + 1][0], Qp[G + 1][1], KF(0), KF(1));
          mma16816(SB[T], Qp[G + 3][0], Qp[G + 3][1], Qp[G + 4][0], Qp[G + 4][1], KF(3), KF(4));
        }
        uint32_t ae, al, ahe, ahl, be, bl, bhe, bhl;
        win_softmax(SA, e0, e1, first, maskE, ae, al, ahe, ahl);
        win_softmax(SB, e0, e1, first, maskE, be, bl, bhe, bhl);
        g_step(4 + 2 * hp);
        float O[6][4];
#pragma unroll
        for (int c = 0; c < 3; c++) {
          mma1688z(O[c], 0u, ahl, Vt[G + c][1]);
          mma1688z(O[3 + c], 0u, bhl, Vt[G + 2 + c][1]);
          mma16816(O[c], ae, 0u, al, ahe, V0[c], Vt[G + c][0]);
          mma16816(O[3 + c], be, 0u, bl, bhe, V0[2 + c], Vt[G + 2 + c][0]);
        }
#pragma unroll
        for (int e = 0; e < 4; e++) O[2][e] = q < 2 ? O[2][e] : O[3][e];
        stsm4(odst + G * 16, pack2(O[0][0], O[0][1]), pack2(O[0][2], O[0][3]), pack2(O[1][0], O[1][1]), pack2(O[1][2], O[1][3]));
        stsm4(odst + (G + 3) * 16, pack2(O[4][0], O[4][1]), pack2(O[4][2], O[4][3]), pack2(O[5][0], O[5][1]), pack2(O[5][2], O[5][3]));
        stsm2(odst + (G + 2) * 16, pack2(O[2][0], O[2][1]), pack2(O[2][2], O[2][3]));
        if (hp == 1) { fence_async_smem(); bar_arrive<2, 288>(); }
        g_step(5 + 2 * hp);
      }
    }
    TS(19 + wg * 16);
    uint32_t b1v[8];
#pragma unroll
    for (int c = 0; c < 8; c++) b1v[c] = __ldg((const uint32_t*)(pt.b1 + gf * 128 + r * 64 + c * 8 + 2 * q));
#pragma unroll 1
    for (int n = 8; n < NG; n++) g_step(n);
    TS(20 + wg * 16);

    float accA[80];
    constexpr int SP = NQ + NG;
    auto po_issue = [&](int n) {
      mbar_wait(FULL(SP + n), PAR(SP + n));
      uint32_t a = base + pA_off(n) + wg * 8 * KB, b = base + pB_off(n);
      wg_fence();
#pragma unroll
      for (int k = 0; k < 4; k++)
        Wgmma<160, 0, 1>::run(accA, mkdesc(a + k * 32, 16, 1024, 1), mkdesc(b + k * 1024, 4096, 512, 2), (n | k) != 0);
      wg_commit();
    };
    po_issue(0);
    wg_wait<1>();
    reg_fence(accG);
    if (lead) mbar_arrive2(EMPTY(SP - 1));
    TS(21 + wg * 16);
    mbar_wait(BAR(B_XFREE1), 0);
    float keep[32];
    {
      const uint32_t rdst = mapa(base + RECVG_OFF + tid * 16, r ^ 1), rbar = mapa(BAR(B_RECVG), r ^ 1);
      if (r == 0) {
#pragma unroll
        for (int c = 0; c < 8; c++) st_async4(rdst + c * 4096, accG[32 + 4 * c], accG[33 + 4 * c], accG[34 + 4 * c], accG[35 + 4 * c], rbar);
#pragma unroll
        for (int c = 0; c < 32; c++) keep[c] = accG[c];
      } else {
#pragma unroll
        for (int c = 0; c < 8; c++) st_async4(rdst + c * 4096, accG[4 * c], accG[1 + 4 * c], accG[2 + 4 * c], accG[3 + 4 * c], rbar);
#pragma unroll
        for (int c = 0; c < 32; c++) keep[c] = accG[32 + c];
      }
    }
    po_issue(1);
    const int prow = pm * 128 + wg * 64 + w * 16 + rho;
    float2 gt0, gt1;
    asm volatile("ld.relaxed.gpu.global.v2.f32 {%0,%1}, [%2];" : "=f"(gt0.x), "=f"(gt0.y) : "l"(g_gate + prow) : "memory");
    asm volatile("ld.relaxed.gpu.global.v2.f32 {%0,%1}, [%2];" : "=f"(gt1.x), "=f"(gt1.y) : "l"(g_gate + prow + 8) : "memory");
    const float b20 = __bfloat162float(pt.b2[prow]), b21 = __bfloat162float(pt.b2[prow + 8]);
    mbar_wait(BAR(B_RECVG), 0);
    TS(22 + wg * 16);
    {
      const int urow = wg * 64 + w * 16 + (lane & 15);
      const uint32_t udst = base + UST_OFF + urow * 128;
#pragma unroll
      for (int hf = 0; hf < 2; hf++) {
#pragma unroll
        for (int c2 = 0; c2 < 2; c2++) {
          uint32_t pk[4];
#pragma unroll
          for (int cc = 0; cc < 2; cc++) {
            const int c = hf * 4 + c2 * 2 + cc;
            float4 v = lds128f(base + RECVG_OFF + tid * 16 + c * 4096);
            float bl_ = bf_lo(b1v[c]), bh_ = bf_hi(b1v[c]);
            pk[2 * cc] = pack2(gelu_tanh(keep[4 * c] + v.x + bl_), gelu_tanh(keep[4 * c + 1] + v.y + bh_));
            pk[2 * cc + 1] = pack2(gelu_tanh(keep[4 * c + 2] + v.z + bl_), gelu_tanh(keep[4 * c + 3] + v.w + bh_));
          }
          stsm4(udst + (((hf * 4 + c2 * 2 + (lane >> 4)) ^ (lane & 7)) << 4), pk[0], pk[1], pk[2], pk[3]);
        }
        if (hf == 0) { wg_wait<1>(); if (lead) mbar_arrive2(EMPTY(SP)); po_issue(2); }
      }
      fence_async_smem();
      bar_arrive<3, 288>();
    }
    TS(23 + wg * 16);
    wg_wait<1>(); if (lead) mbar_arrive2(EMPTY(SP + 1));
    po_issue(3);
    wg_wait<1>(); if (lead) mbar_arrive2(EMPTY(SP + 2));
    po_issue(4);
    wg_wait<1>(); if (lead) mbar_arrive2(EMPTY(SP + 3));
    TS(24 + wg * 16);
    float accY[80];
#pragma unroll 1
    for (int n = NPO; n < NPO + NPY; n++) {
      mbar_wait(FULL(SP + n), PAR(SP + n));
      if (n == NPO) TS(25 + wg * 16);
      uint32_t a = base + pA_off(n) + wg * 8 * KB, b = base + pB_off(n);
      wg_fence();
#pragma unroll
      for (int k = 0; k < 4; k++)
        Wgmma<160, 1, 0>::run(accY, mkdesc(a + k * 2048, 8192, 1024, 1), mkdesc(b + k * 32, 16, 1024, 1), (n != NPO) || k != 0);
      wg_commit();
      wg_wait<1>();
      if (lead) mbar_arrive2(EMPTY(SP + n - 1));
    }
    mbar_wait(BAR(B_XFREE2), 0);
    wg_wait<0>();
    reg_fence(accA); reg_fence(accY);
    TS(26 + wg * 16);
    {
      const uint32_t rdst = mapa(base + RECVP_OFF + tid * 16, r ^ 1), rbar = mapa(BAR(B_RECVP), r ^ 1);
      float kp[40];
      const float c0 = gt0.y * b20, c1 = gt1.y * b21;
      auto mix = [&](int e, float add) { const float2 gt = (e & 2) ? gt1 : gt0; return fmaf(gt.x, accA[e], fmaf(gt.y, accY[e], add)); };
      if (r == 0) {
#pragma unroll
        for (int c = 0; c < 10; c++) st_async4(rdst + c * 4096, mix(40 + 4 * c, 0.f), mix(41 + 4 * c, 0.f), mix(42 + 4 * c, 0.f), mix(43 + 4 * c, 0.f), rbar);
#pragma unroll
        for (int e = 0; e < 40; e++) kp[e] = mix(e, (e & 2) ? c1 : c0);
      } else {
#pragma unroll
        for (int c = 0; c < 10; c++) st_async4(rdst + c * 4096, mix(4 * c, 0.f), mix(1 + 4 * c, 0.f), mix(2 + 4 * c, 0.f), mix(3 + 4 * c, 0.f), rbar);
#pragma unroll
        for (int e = 0; e < 40; e++) kp[e] = mix(40 + e, (e & 2) ? c1 : c0);
      }
      mbar_wait(BAR(B_RECVP), 0);
      TS(27 + wg * 16);
      const uint32_t ostg = base + OUTST_OFF + warp * 2560;
      const uint32_t odst = ostg + (lane & 15) * 160 + (lane >> 4) * 16;
#pragma unroll
      for (int c2 = 0; c2 < 5; c2++) {
        float4 v0 = lds128f(base + RECVP_OFF + tid * 16 + (2 * c2) * 4096), v1 = lds128f(base + RECVP_OFF + tid * 16 + (2 * c2 + 1) * 4096);
        const float* k0 = kp + 8 * c2;
        stsm4(odst + c2 * 32, pack2(k0[0] + v0.x, k0[1] + v0.y), pack2(k0[2] + v0.z, k0[3] + v0.w), pack2(k0[4] + v1.x, k0[5] + v1.y), pack2(k0[6] + v1.z, k0[7] + v1.w));
      }
      fence_async_smem();
      __syncwarp();
      if (lane == 0) {
        tma2d_st(&mp.out, pn * 160 + r * 80, pm * 128 + warp * 16, ostg);
        bulk_commit(); bulk_wait0_read();
      }
      TS(28 + wg * 16);
    }
    }
  }
}

typedef CUresult (*EncFn)(CUtensorMap*, CUtensorMapDataType, cuuint32_t, void*, const cuuint64_t*, const cuuint64_t*, const cuuint32_t*,
                          const cuuint32_t*, CUtensorMapInterleave, CUtensorMapSwizzle, CUtensorMapL2promotion, CUtensorMapFloatOOBfill);

void mkmap(EncFn enc, CUtensorMap* m, const void* ptr, int rank, cuuint64_t d0, cuuint64_t d1, cuuint64_t d2, cuuint64_t s1, cuuint64_t s2,
           cuuint32_t b0, cuuint32_t b1, cuuint32_t b2, CUtensorMapSwizzle sw) {
  cuuint64_t dims[3] = {d0, d1, d2}, st[2] = {s1, s2};
  cuuint32_t box[3] = {b0, b1, b2}, es[3] = {1, 1, 1};
  enc(m, CU_TENSOR_MAP_DATA_TYPE_BFLOAT16, rank, (void*)ptr, dims, st, box, es, CU_TENSOR_MAP_INTERLEAVE_NONE, sw,
      CU_TENSOR_MAP_L2_PROMOTION_L2_128B, CU_TENSOR_MAP_FLOAT_OOB_FILL_NONE);
}

}

extern "C" void kernel_launch(void* const* d_in, const int* in_sizes, int n_in, void* d_out, int out_size) {
  (void)in_sizes; (void)n_in; (void)out_size;
  const __nv_bfloat16* x = (const __nv_bfloat16*)d_in[0];
  const __nv_bfloat16* wqkv = (const __nv_bfloat16*)d_in[1];
  const __nv_bfloat16* wo = (const __nv_bfloat16*)d_in[2];
  const __nv_bfloat16* w1 = (const __nv_bfloat16*)d_in[4];
  const __nv_bfloat16* w2 = (const __nv_bfloat16*)d_in[6];
  void* fn = nullptr; cudaDriverEntryPointQueryResult qr;
  cudaGetDriverEntryPoint("cuTensorMapEncodeTiled", &fn, cudaEnableDefault, &qr);
  EncFn enc = (EncFn)fn;
  void *ph, *po, *pu;
  cudaGetSymbolAddress(&ph, g_h); cudaGetSymbolAddress(&po, g_o); cudaGetSymbolAddress(&pu, g_u);
  const CUtensorMapSwizzle S128 = CU_TENSOR_MAP_SWIZZLE_128B, S64 = CU_TENSOR_MAP_SWIZZLE_64B, S0 = CU_TENSOR_MAP_SWIZZLE_NONE;
  Maps mp;
  mkmap(enc, &mp.x, x, 3, 640, 1024, 2, 2560, 1280, 64, 64, 2, S128);
  mkmap(enc, &mp.wqm, wqkv, 3, 640, 640, 3, 3840, 1280, 64, 32, 3, S128);
  mkmap(enc, &mp.wqr, wqkv, 3, 640, 640, 3, 3840, 1280, 16, 32, 3, CU_TENSOR_MAP_SWIZZLE_32B);
  mkmap(enc, &mp.h, ph, 3, 64, 2048, 10, 1280, 128, 64, 64, 2, S128);
  mkmap(enc, &mp.w1, w1, 3, 64, 2048, 24, 3072, 128, 64, 64, 2, S128);
  mkmap(enc, &mp.old_, po, 2, 640, 2048, 1, 1280, 0, 64, 128, 1, S128);
  mkmap(enc, &mp.wo, wo, 3, 32, 640, 20, 1280, 64, 32, 64, 5, S64);
  mkmap(enc, &mp.w2, w2, 3, 64, 1536, 32, 4096, 128, 64, 64, 2, S128);
  mkmap(enc, &mp.uld, pu, 2, 1536, 640, 1, 3072, 0, 64, 160, 1, S128);
  mkmap(enc, &mp.ost, po, 3, 640, 1024, 2, 2560, 1280, 80, 64, 2, S0);
  mkmap(enc, &mp.ust, pu, 2, 1536, 640, 1, 3072, 0, 64, 128, 1, S128);
  mkmap(enc, &mp.out, d_out, 2, 640, 2048, 1, 1280, 0, 80, 16, 1, S0);
  Ptrs pt;
  pt.x = x; pt.b1 = (const __nv_bfloat16*)d_in[5]; pt.b2 = (const __nv_bfloat16*)d_in[7]; pt.gw = (const __nv_bfloat16*)d_in[8];
  int dev = 0, sms = 0;
  cudaGetDevice(&dev);
  cudaDeviceGetAttribute(&sms, cudaDevAttrMultiProcessorCount, dev);
  pt.smid_mode = (sms == 132);
  cudaFuncSetAttribute(fused_kernel, cudaFuncAttributeMaxDynamicSharedMemorySize, SMEM_BYTES);
  fused_kernel<<<pt.smid_mode ? 132 : 128, 384, SMEM_BYTES, cudaStreamPerThread>>>(mp, pt);
}
```

```cpp
#include <cuda_runtime.h>
#include <cuda_bf16.h>
#include <cuda.h>
#include <stdint.h>
#include <stddef.h>

namespace {

constexpr int S_ = 2048, D_ = 640, F_ = 1536;
constexpr int NQ = 10, NG = 16, NPO = 5, NPY = 12, SP = NQ + NG, NP = NPO + NPY, NSTEP = SP + NP;
constexpr int KB = 1024;
constexpr int OST_OFF = 160 * KB;
constexpr int RECV_OFF = 180 * KB;
constexpr int OUTST_OFF = 96 * KB;
constexpr int HALO_OFF = 200 * KB;
constexpr int HST_OFF0 = 144 * KB, HST_OFF1 = 208 * KB, HPITCH = 1296;
constexpr int BAR_OFF = 225 * KB;
constexpr int B1_OFF = BAR_OFF + 896 + 128;
constexpr int SMEM_BYTES = 227 * KB;
constexpr int B_EMPTY = 48, B_HREADY = 96  , B_HALO = 100, B_OREADY = 101, B_UREADY = 102  ,
              B_RECVG = 104  , B_RECVP = 43  , B_XFREE = 106, B_LNDONE = 107, LNCNT = 108  ;
#define LEADG 3
#define PF 1
#define PFSTART 5000
#define GSTAG 420
#define PSTAG 0
#define ALIGN 1
#define EPF 1
#define USTAG 450
#define NOLN 0
#define KPO 0
#define GMAP 0
#define PMAP 1
constexpr int LEADP = 4;
#define STAGGER 750
#define ATT0 8

struct Maps { CUtensorMap x, wqm, wqr, h, w1, old_, wo, w2, uld, ost, ust, out; };
struct Scratch {
  __nv_bfloat16 h[S_ * D_], o[S_ * D_], u[D_ * F_];
  uint4 halo[136 * 320];
  float4 gate[S_];
  unsigned cnt[(8 + 4 + 32 + 136 + 128) * 32];
};
constexpr int C_H = 0, C_U = 8, C_O = 12, C_HALO = 44, C_EP = 180;
struct Ptrs { Scratch* sc; const __nv_bfloat16 *x, *wq, *gw, *b1, *b2; const __nv_bfloat16 *w2, *wo; };
__device__ __align__(1024) Scratch g_sc;
#define TSG(grp, i)

__device__ __forceinline__ int clk() { int c; asm volatile("mov.u32 %0, %%clock;" : "=r"(c)); return c; }
template <int N, int TA, int TB, uint32_t HA, uint32_t HB> struct Wgmma;
template <int TA, int TB, uint32_t HA, uint32_t HB> struct Wgmma<48, TA, TB, HA, HB> {
  static __device__ __forceinline__ void run(float (&d)[24], uint32_t la, uint32_t lb, int sd) {
    asm volatile("{\n.reg .pred p;\n.reg .b64 da, db;\nsetp.ne.b32 p, %26, 0;\nmov.b64 da, {%24, %29};\nmov.b64 db, {%25, %30};\n"
      "wgmma.mma_async.sync.aligned.m64n48k16.f32.bf16.bf16 {%0, %1, %2, %3, %4, %5, %6, %7, %8, %9, %10, %11, %12, %13, %14, %15, %16, %17, %18, %19, %20, %21, %22, %23}, da, db, p, 1, 1, %27, %28;\n}\n"
      : "+f"(d[0]), "+f"(d[1]), "+f"(d[2]), "+f"(d[3]), "+f"(d[4]), "+f"(d[5]), "+f"(d[6]), "+f"(d[7]), "+f"(d[8]), "+f"(d[9]), "+f"(d[10]), "+f"(d[11]), "+f"(d[12]), "+f"(d[13]), "+f"(d[14]), "+f"(d[15]), "+f"(d[16]), "+f"(d[17]), "+f"(d[18]), "+f"(d[19]), "+f"(d[20]), "+f"(d[21]), "+f"(d[22]), "+f"(d[23])
      : "r"(la), "r"(lb), "r"(sd), "n"(TA), "n"(TB), "n"(HA), "n"(HB));
  }
};
template <int TA, int TB, uint32_t HA, uint32_t HB> struct Wgmma<128, TA, TB, HA, HB> {
  static __device__ __forceinline__ void run(float (&d)[64], uint32_t la, uint32_t lb, int sd) {
    asm volatile("{\n.reg .pred p;\n.reg .b64 da, db;\nsetp.ne.b32 p, %66, 0;\nmov.b64 da, {%64, %69};\nmov.b64 db, {%65, %70};\n"
      "wgmma.mma_async.sync.aligned.m64n128k16.f32.bf16.bf16 {%0, %1, %2, %3, %4, %5, %6, %7, %8, %9, %10, %11, %12, %13, %14, %15, %16, %17, %18, %19, %20, %21, %22, %23, %24, %25, %26, %27, %28, %29, %30, %31, %32, %33, %34, %35, %36, %37, %38, %39, %40, %41, %42, %43, %44, %45, %46, %47, %48, %49, %50, %51, %52, %53, %54, %55, %56, %57, %58, %59, %60, %61, %62, %63}, da, db, p, 1, 1, %67, %68;\n}\n"
      : "+f"(d[0]), "+f"(d[1]), "+f"(d[2]), "+f"(d[3]), "+f"(d[4]), "+f"(d[5]), "+f"(d[6]), "+f"(d[7]), "+f"(d[8]), "+f"(d[9]), "+f"(d[10]), "+f"(d[11]), "+f"(d[12]), "+f"(d[13]), "+f"(d[14]), "+f"(d[15]), "+f"(d[16]), "+f"(d[17]), "+f"(d[18]), "+f"(d[19]), "+f"(d[20]), "+f"(d[21]), "+f"(d[22]), "+f"(d[23]), "+f"(d[24]), "+f"(d[25]), "+f"(d[26]), "+f"(d[27]), "+f"(d[28]), "+f"(d[29]), "+f"(d[30]), "+f"(d[31]), "+f"(d[32]), "+f"(d[33]), "+f"(d[34]), "+f"(d[35]), "+f"(d[36]), "+f"(d[37]), "+f"(d[38]), "+f"(d[39]), "+f"(d[40]), "+f"(d[41]), "+f"(d[42]), "+f"(d[43]), "+f"(d[44]), "+f"(d[45]), "+f"(d[46]), "+f"(d[47]), "+f"(d[48]), "+f"(d[49]), "+f"(d[50]), "+f"(d[51]), "+f"(d[52]), "+f"(d[53]), "+f"(d[54]), "+f"(d[55]), "+f"(d[56]), "+f"(d[57]), "+f"(d[58]), "+f"(d[59]), "+f"(d[60]), "+f"(d[61]), "+f"(d[62]), "+f"(d[63])
      : "r"(la), "r"(lb), "r"(sd), "n"(TA), "n"(TB), "n"(HA), "n"(HB));
  }
};
template <int TA, int TB, uint32_t HA, uint32_t HB> struct Wgmma<160, TA, TB, HA, HB> {
  static __device__ __forceinline__ void run(float (&d)[80], uint32_t la, uint32_t lb, int sd) {
    asm volatile("{\n.reg .pred p;\n.reg .b64 da, db;\nsetp.ne.b32 p, %82, 0;\nmov.b64 da, {%80, %85};\nmov.b64 db, {%81, %86};\n"
      "wgmma.mma_async.sync.aligned.m64n160k16.f32.bf16.bf16 {%0, %1, %2, %3, %4, %5, %6, %7, %8, %9, %10, %11, %12, %13, %14, %15, %16, %17, %18, %19, %20, %21, %22, %23, %24, %25, %26, %27, %28, %29, %30, %31, %32, %33, %34, %35, %36, %37, %38, %39, %40, %41, %42, %43, %44, %45, %46, %47, %48, %49, %50, %51, %52, %53, %54, %55, %56, %57, %58, %59, %60, %61, %62, %63, %64, %65, %66, %67, %68, %69, %70, %71, %72, %73, %74, %75, %76, %77, %78, %79}, da, db, p, 1, 1, %83, %84;\n}\n"
      : "+f"(d[0]), "+f"(d[1]), "+f"(d[2]), "+f"(d[3]), "+f"(d[4]), "+f"(d[5]), "+f"(d[6]), "+f"(d[7]), "+f"(d[8]), "+f"(d[9]), "+f"(d[10]), "+f"(d[11]), "+f"(d[12]), "+f"(d[13]), "+f"(d[14]), "+f"(d[15]), "+f"(d[16]), "+f"(d[17]), "+f"(d[18]), "+f"(d[19]), "+f"(d[20]), "+f"(d[21]), "+f"(d[22]), "+f"(d[23]), "+f"(d[24]), "+f"(d[25]), "+f"(d[26]), "+f"(d[27]), "+f"(d[28]), "+f"(d[29]), "+f"(d[30]), "+f"(d[31]), "+f"(d[32]), "+f"(d[33]), "+f"(d[34]), "+f"(d[35]), "+f"(d[36]), "+f"(d[37]), "+f"(d[38]), "+f"(d[39]), "+f"(d[40]), "+f"(d[41]), "+f"(d[42]), "+f"(d[43]), "+f"(d[44]), "+f"(d[45]), "+f"(d[46]), "+f"(d[47]), "+f"(d[48]), "+f"(d[49]), "+f"(d[50]), "+f"(d[51]), "+f"(d[52]), "+f"(d[53]), "+f"(d[54]), "+f"(d[55]), "+f"(d[56]), "+f"(d[57]), "+f"(d[58]), "+f"(d[59]), "+f"(d[60]), "+f"(d[61]), "+f"(d[62]), "+f"(d[63]), "+f"(d[64]), "+f"(d[65]), "+f"(d[66]), "+f"(d[67]), "+f"(d[68]), "+f"(d[69]), "+f"(d[70]), "+f"(d[71]), "+f"(d[72]), "+f"(d[73]), "+f"(d[74]), "+f"(d[75]), "+f"(d[76]), "+f"(d[77]), "+f"(d[78]), "+f"(d[79])
      : "r"(la), "r"(lb), "r"(sd), "n"(TA), "n"(TB), "n"(HA), "n"(HB));
  }
};
template <int TA, int TB, uint32_t HA, uint32_t HB> struct Wgmma<192, TA, TB, HA, HB> {
  static __device__ __forceinline__ void run(float (&d)[96], uint32_t la, uint32_t lb, int sd) {
    asm volatile("{\n.reg .pred p;\n.reg .b64 da, db;\nsetp.ne.b32 p, %98, 0;\nmov.b64 da, {%96, %101};\nmov.b64 db, {%97, %102};\n"
      "wgmma.mma_async.sync.aligned.m64n192k16.f32.bf16.bf16 {%0, %1, %2, %3, %4, %5, %6, %7, %8, %9, %10, %11, %12, %13, %14, %15, %16, %17, %18, %19, %20, %21, %22, %23, %24, %25, %26, %27, %28, %29, %30, %31, %32, %33, %34, %35, %36, %37, %38, %39, %40, %41, %42, %43, %44, %45, %46, %47, %48, %49, %50, %51, %52, %53, %54, %55, %56, %57, %58, %59, %60, %61, %62, %63, %64, %65, %66, %67, %68, %69, %70, %71, %72, %73, %74, %75, %76, %77, %78, %79, %80, %81, %82, %83, %84, %85, %86, %87, %88, %89, %90, %91, %92, %93, %94, %95}, da, db, p, 1, 1, %99, %100;\n}\n"
      : "+f"(d[0]), "+f"(d[1]), "+f"(d[2]), "+f"(d[3]), "+f"(d[4]), "+f"(d[5]), "+f"(d[6]), "+f"(d[7]), "+f"(d[8]), "+f"(d[9]), "+f"(d[10]), "+f"(d[11]), "+f"(d[12]), "+f"(d[13]), "+f"(d[14]), "+f"(d[15]), "+f"(d[16]), "+f"(d[17]), "+f"(d[18]), "+f"(d[19]), "+f"(d[20]), "+f"(d[21]), "+f"(d[22]), "+f"(d[23]), "+f"(d[24]), "+f"(d[25]), "+f"(d[26]), "+f"(d[27]), "+f"(d[28]), "+f"(d[29]), "+f"(d[30]), "+f"(d[31]), "+f"(d[32]), "+f"(d[33]), "+f"(d[34]), "+f"(d[35]), "+f"(d[36]), "+f"(d[37]), "+f"(d[38]), "+f"(d[39]), "+f"(d[40]), "+f"(d[41]), "+f"(d[42]), "+f"(d[43]), "+f"(d[44]), "+f"(d[45]), "+f"(d[46]), "+f"(d[47]), "+f"(d[48]), "+f"(d[49]), "+f"(d[50]), "+f"(d[51]), "+f"(d[52]), "+f"(d[53]), "+f"(d[54]), "+f"(d[55]), "+f"(d[56]), "+f"(d[57]), "+f"(d[58]), "+f"(d[59]), "+f"(d[60]), "+f"(d[61]), "+f"(d[62]), "+f"(d[63]), "+f"(d[64]), "+f"(d[65]), "+f"(d[66]), "+f"(d[67]), "+f"(d[68]), "+f"(d[69]), "+f"(d[70]), "+f"(d[71]), "+f"(d[72]), "+f"(d[73]), "+f"(d[74]), "+f"(d[75]), "+f"(d[76]), "+f"(d[77]), "+f"(d[78]), "+f"(d[79]), "+f"(d[80]), "+f"(d[81]), "+f"(d[82]), "+f"(d[83]), "+f"(d[84]), "+f"(d[85]), "+f"(d[86]), "+f"(d[87]), "+f"(d[88]), "+f"(d[89]), "+f"(d[90]), "+f"(d[91]), "+f"(d[92]), "+f"(d[93]), "+f"(d[94]), "+f"(d[95])
      : "r"(la), "r"(lb), "r"(sd), "n"(TA), "n"(TB), "n"(HA), "n"(HB));
  }
};

__device__ __forceinline__ uint32_t smem_u32(const void* p) { return (uint32_t)__cvta_generic_to_shared(p); }
__device__ __forceinline__ void mbar_init(uint32_t bar, int cnt) { asm volatile("mbarrier.init.shared::cta.b64 [%0], %1;" ::"r"(bar), "r"(cnt) : "memory"); }
__device__ __forceinline__ void mbar_expect_tx(uint32_t bar, uint32_t bytes) { asm volatile("mbarrier.arrive.expect_tx.shared::cta.b64 _, [%0], %1;" ::"r"(bar), "r"(bytes) : "memory"); }
__device__ __forceinline__ void mbar_arrive(uint32_t bar) { asm volatile("mbarrier.arrive.shared::cta.b64 _, [%0];" ::"r"(bar) : "memory"); }
__device__ __forceinline__ uint32_t mapa(uint32_t a, uint32_t cta) { uint32_t r; asm("mapa.shared::cluster.u32 %0, %1, %2;" : "=r"(r) : "r"(a), "r"(cta)); return r; }
__device__ __forceinline__ void mbar_arrive_remote(uint32_t rbar) { asm volatile("mbarrier.arrive.shared::cluster.b64 _, [%0];" ::"r"(rbar) : "memory"); }
__device__ __forceinline__ void mbar_wait(uint32_t bar) {
  asm volatile("{\n.reg .pred p;\nW_LOOP:\nmbarrier.try_wait.parity.shared::cta.b64 p, [%0], 0;\n@!p bra.uni W_LOOP;\n}" ::"r"(bar) : "memory");
}
__device__ __forceinline__ bool mbar_try(uint32_t bar) {
  uint32_t ok;
  asm volatile("{\n.reg .pred p;\nmbarrier.test_wait.parity.shared::cta.b64 p, [%1], 0;\nselp.b32 %0, 1, 0, p;\n}" : "=r"(ok) : "r"(bar) : "memory");
  return ok;
}
__device__ __forceinline__ bool elect() {
  uint32_t ok;
  asm volatile("{\n.reg .pred p;\nelect.sync _|p, 0xffffffff;\nselp.b32 %0, 1, 0, p;\n}" : "=r"(ok));
  return ok;
}
__device__ __forceinline__ void tma2d(uint32_t dst, const CUtensorMap* m, int c0, int c1, uint32_t bar) {
  asm volatile("cp.async.bulk.tensor.2d.shared::cluster.global.mbarrier::complete_tx::bytes [%0], [%1, {%3,%4}], [%2];" ::"r"(dst), "l"(m), "r"(bar), "r"(c0), "r"(c1) : "memory");
}
__device__ __forceinline__ void tma3d(uint32_t dst, const CUtensorMap* m, int c0, int c1, int c2, uint32_t bar) {
  asm volatile("cp.async.bulk.tensor.3d.shared::cluster.global.mbarrier::complete_tx::bytes [%0], [%1, {%3,%4,%5}], [%2];" ::"r"(dst), "l"(m), "r"(bar), "r"(c0), "r"(c1), "r"(c2) : "memory");
}
__device__ __forceinline__ void tma3d_mc(uint32_t dst, const CUtensorMap* m, int c0, int c1, int c2, uint32_t bar) {
  asm volatile("cp.async.bulk.tensor.3d.shared::cluster.global.mbarrier::complete_tx::bytes.multicast::cluster [%0], [%1, {%3,%4,%5}], [%2], %6;" ::"r"(dst), "l"(m), "r"(bar), "r"(c0), "r"(c1), "r"(c2), "h"((uint16_t)3) : "memory");
}
__device__ __forceinline__ void tma2d_st(const CUtensorMap* m, int c0, int c1, uint32_t src) {
  asm volatile("cp.async.bulk.tensor.2d.global.shared::cta.bulk_group [%0, {%2,%3}], [%1];" ::"l"(m), "r"(src), "r"(c0), "r"(c1) : "memory");
}
__device__ __forceinline__ void tma3d_st(const CUtensorMap* m, int c0, int c1, int c2, uint32_t src) {
  asm volatile("cp.async.bulk.tensor.3d.global.shared::cta.bulk_group [%0, {%2,%3,%4}], [%1];" ::"l"(m), "r"(src), "r"(c0), "r"(c1), "r"(c2) : "memory");
}
__device__ __forceinline__ void bulk_commit() { asm volatile("cp.async.bulk.commit_group;" ::: "memory"); }
__device__ __forceinline__ void bulk_wait0() { asm volatile("cp.async.bulk.wait_group 0;" ::: "memory"); }
__device__ __forceinline__ void fence_async_smem() { asm volatile("fence.proxy.async.shared::cta;" ::: "memory"); }
__device__ __forceinline__ void wg_fence() { asm volatile("wgmma.fence.sync.aligned;" ::: "memory"); }
__device__ __forceinline__ void wg_commit() { asm volatile("wgmma.commit_group.sync.aligned;" ::: "memory"); }
template <int N> __device__ __forceinline__ void wg_wait() { asm volatile("wgmma.wait_group.sync.aligned %0;" ::"n"(N) : "memory"); }
template <int N> __device__ __forceinline__ void reg_fence(float (&a)[N]) {
#pragma unroll
  for (int i = 0; i < N; i++) asm volatile("" : "+f"(a[i])::"memory");
}
template <int ID, int N> __device__ __forceinline__ void bar_sync() { asm volatile("bar.sync %0, %1;" ::"n"(ID), "n"(N) : "memory"); }
template <int ID, int N> __device__ __forceinline__ void bar_arrive() { asm volatile("bar.arrive %0, %1;" ::"n"(ID), "n"(N) : "memory"); }
__host__ __device__ constexpr uint32_t dlo(uint32_t off, uint32_t lbo) { return (off >> 4) | ((lbo >> 4) << 16); }
__host__ __device__ constexpr uint32_t dhi(uint32_t sbo, uint32_t swz) { return (sbo >> 4) | (swz << 30); }
constexpr uint32_t H128 = dhi(1024, 1), H64 = dhi(512, 2), H32 = dhi(256, 3);
__device__ __forceinline__ uint32_t pack2(float lo, float hi) { uint32_t r; asm("cvt.rn.bf16x2.f32 %0, %1, %2;" : "=r"(r) : "f"(hi), "f"(lo)); return r; }
__device__ __forceinline__ float bf_lo(uint32_t v) { return __uint_as_float(v << 16); }
__device__ __forceinline__ float bf_hi(uint32_t v) { return __uint_as_float(v & 0xFFFF0000u); }
__device__ __forceinline__ float bf_round(float v) { return __bfloat162float(__float2bfloat16_rn(v)); }
__device__ __forceinline__ uint32_t movm(uint32_t a) { uint32_t d; asm volatile("movmatrix.sync.aligned.m8n8.trans.b16 %0, %1;" : "=r"(d) : "r"(a)); return d; }
__device__ __forceinline__ void stsm4(uint32_t addr, uint32_t a, uint32_t b, uint32_t c, uint32_t d) {
  asm volatile("stmatrix.sync.aligned.m8n8.x4.shared.b16 [%0], {%1,%2,%3,%4};" ::"r"(addr), "r"(a), "r"(b), "r"(c), "r"(d) : "memory");
}
__device__ __forceinline__ void stsm2(uint32_t addr, uint32_t a, uint32_t b) {
  asm volatile("stmatrix.sync.aligned.m8n8.x2.shared.b16 [%0], {%1,%2};" ::"r"(addr), "r"(a), "r"(b) : "memory");
}
__device__ __forceinline__ void sts128(uint32_t addr, uint32_t a, uint32_t b, uint32_t c, uint32_t d) {
  asm volatile("st.shared.v4.b32 [%0], {%1,%2,%3,%4};" ::"r"(addr), "r"(a), "r"(b), "r"(c), "r"(d) : "memory");
}
__device__ __forceinline__ void sts64(uint32_t addr, uint32_t a, uint32_t b) { asm volatile("st.shared.v2.b32 [%0], {%1,%2};" ::"r"(addr), "r"(a), "r"(b) : "memory"); }
__device__ __forceinline__ uint4 lds128(uint32_t addr) { uint4 v; asm volatile("ld.shared.v4.b32 {%0,%1,%2,%3}, [%4];" : "=r"(v.x), "=r"(v.y), "=r"(v.z), "=r"(v.w) : "r"(addr) : "memory"); return v; }
__device__ __forceinline__ uint32_t hmul2(uint32_t a, uint32_t b) { uint32_t d; asm("mul.rn.bf16x2 %0, %1, %2;" : "=r"(d) : "r"(a), "r"(b)); return d; }
__device__ __forceinline__ uint32_t hsub2(uint32_t a, uint32_t b) { uint32_t d; asm("sub.rn.bf16x2 %0, %1, %2;" : "=r"(d) : "r"(a), "r"(b)); return d; }
__device__ __forceinline__ void mma16816(float (&c)[4], uint32_t a0, uint32_t a1, uint32_t a2, uint32_t a3, uint32_t b0, uint32_t b1) {
  asm volatile("mma.sync.aligned.m16n8k16.row.col.f32.bf16.bf16.f32 {%0,%1,%2,%3}, {%4,%5,%6,%7}, {%8,%9}, {%0,%1,%2,%3};"
               : "+f"(c[0]), "+f"(c[1]), "+f"(c[2]), "+f"(c[3]) : "r"(a0), "r"(a1), "r"(a2), "r"(a3), "r"(b0), "r"(b1));
}
__device__ __forceinline__ void mma1688z(float (&c)[4], uint32_t a0, uint32_t a1, uint32_t b0) {
  asm volatile("mma.sync.aligned.m16n8k8.row.col.f32.bf16.bf16.f32 {%0,%1,%2,%3}, {%4,%5}, {%6}, {%7,%7,%7,%7};"
               : "=f"(c[0]), "=f"(c[1]), "=f"(c[2]), "=f"(c[3]) : "r"(a0), "r"(a1), "r"(b0), "f"(0.f));
}
__device__ __forceinline__ unsigned ld_relaxed(const unsigned* p) { unsigned v; asm volatile("ld.relaxed.gpu.global.u32 %0, [%1];" : "=r"(v) : "l"(p) : "memory"); return v; }
__device__ __forceinline__ void red_flag(unsigned* p) { asm volatile("red.relaxed.gpu.global.inc.u32 [%0], 0xffffffff;" ::"l"(p) : "memory"); }
__device__ __forceinline__ void bulk_st(void* g, uint32_t src, uint32_t bytes) {
  asm volatile("cp.async.bulk.global.shared::cta.bulk_group [%0], [%1], %2;" ::"l"(g), "r"(src), "r"(bytes) : "memory");
}
__device__ __forceinline__ void bulk_ld(uint32_t dst, const void* g, uint32_t bytes, uint32_t bar) {
  asm volatile("cp.async.bulk.shared::cluster.global.mbarrier::complete_tx::bytes [%0], [%1], %2, [%3];" ::"r"(dst), "l"(g), "r"(bytes), "r"(bar) : "memory");
}
__device__ __forceinline__ uint2 ldg64(const uint2* p) { uint2 v; asm volatile("ld.global.nc.v2.u32 {%0,%1}, [%2];" : "=r"(v.x), "=r"(v.y) : "l"(p)); return v; }
__device__ __forceinline__ void sched_fence(uint32_t zero) {
  asm volatile("{\n.reg .pred p;\nsetp.ne.u32 p, %0, 0;\nSF_LOOP:\n@p bra.uni SF_LOOP;\n}" ::"r"(zero) : "memory");
}
__device__ __forceinline__ void st_async4(uint32_t raddr, uint32_t a, uint32_t b, uint32_t c, uint32_t d, uint32_t rbar) {
  asm volatile("st.async.weak.shared::cluster.mbarrier::complete_tx::bytes.v4.b32 [%0], {%1,%2,%3,%4}, [%5];" ::"r"(raddr), "r"(a), "r"(b), "r"(c), "r"(d), "r"(rbar) : "memory");
}
__device__ __forceinline__ void lds64(uint32_t addr, uint32_t& a, uint32_t& b) { asm volatile("ld.shared.v2.b32 {%0,%1}, [%2];" : "=r"(a), "=r"(b) : "r"(addr) : "memory"); }
__device__ __forceinline__ void l2_prefetch(const void* g, uint32_t bytes) { asm volatile("cp.async.bulk.prefetch.L2.global [%0], %1;" ::"l"(g), "r"(bytes) : "memory"); }
__device__ __forceinline__ uint32_t hadd2(uint32_t a, uint32_t b) { uint32_t d; asm("add.rn.bf16x2 %0, %1, %2;" : "=r"(d) : "r"(a), "r"(b)); return d; }
__device__ __forceinline__ uint32_t hfma2(uint32_t a, uint32_t b, uint32_t c) { uint32_t d; asm("fma.rn.bf16x2 %0, %1, %2, %3;" : "=r"(d) : "r"(a), "r"(b), "r"(c)); return d; }
__device__ __forceinline__ uint32_t hmax2(uint32_t a, uint32_t b) { uint32_t d; asm("max.bf16x2 %0, %1, %2;" : "=r"(d) : "r"(a), "r"(b)); return d; }
__device__ __forceinline__ float rcp(float x) { float y; asm("rcp.approx.ftz.f32 %0, %1;" : "=f"(y) : "f"(x)); return y; }
__device__ __forceinline__ float ex2(float x) { float y; asm("ex2.approx.ftz.f32 %0, %1;" : "=f"(y) : "f"(x)); return y; }
__device__ __forceinline__ float gelu_half(float y) {
  float z = y * fmaf(y * y, 8.f * 0.044715f * 0.7978845608028654f, 2.f * 0.7978845608028654f), t;
  asm("tanh.approx.f32 %0, %1;" : "=f"(t) : "f"(z));
  return fmaf(y, t, y);
}
__device__ __forceinline__ void ldsm4(uint32_t addr, uint32_t& a, uint32_t& b, uint32_t& c, uint32_t& d) {
  asm volatile("ldmatrix.sync.aligned.m8n8.x4.shared.b16 {%0,%1,%2,%3}, [%4];" : "=r"(a), "=r"(b), "=r"(c), "=r"(d) : "r"(addr) : "memory");
}

__host__ __device__ constexpr uint32_t q_off(int s) { return ((0xA630u >> (4 * (s & 3))) & 15) * 16 * KB; }
__host__ __device__ constexpr uint32_t g_off(int n) { return (uint32_t)((0x2103421034210534ull >> (4 * n)) & 15) * 32 * KB; }
__host__ __device__ constexpr uint32_t pa_off(int sl) { return (uint32_t)((0x0E05182029ull >> (8 * sl)) & 255) * 4 * KB; }
__host__ __device__ constexpr uint32_t pb_off(int sl) { return (uint32_t)((0x1209002432ull >> (8 * sl)) & 255) * 4 * KB; }

__device__ __forceinline__ void win_softmax(const float (&S)[3][4], bool e0, bool e1, uint32_t inv0, uint32_t inv1, uint32_t& P0, uint32_t& P1) {
  const uint32_t NEG = 0xCF85u;
  const float L2E = 0.22360679774997896f * 1.4426950408889634f;
  uint32_t A = pack2(e0 ? S[0][0] : S[1][0], e0 ? S[1][2] : S[2][2]);
  uint32_t B = pack2(e1 ? S[0][1] : S[1][1], e1 ? S[1][3] : S[2][3]);
  A = (A & ~inv0) | (NEG & inv0); B = (B & ~inv1) | (NEG & inv1);
  uint32_t m = hmax2(A, B);
  m = hmax2(m, __shfl_xor_sync(0xffffffffu, m, 1));
  m = hmax2(m, __shfl_xor_sync(0xffffffffu, m, 2));
  const float m0 = -bf_lo(m) * L2E, m1 = -bf_hi(m) * L2E;
  P0 = pack2(ex2(fmaf(bf_lo(A), L2E, m0)), ex2(fmaf(bf_lo(B), L2E, m0)));
  P1 = pack2(ex2(fmaf(bf_hi(A), L2E, m1)), ex2(fmaf(bf_hi(B), L2E, m1)));
}

template <bool SMID>
__global__ void __cluster_dims__(2, 1, 1) __launch_bounds__(512, 1)
fused_kernel(const Ptrs pt, const __grid_constant__ Maps mp) {
  extern __shared__ __align__(1024) uint8_t smem_raw[];
  const uint32_t base = smem_u32(smem_raw);
  const uint32_t bars = base + BAR_OFF;
  const int tid = threadIdx.x, lane = tid & 31;
  const int warp = __shfl_sync(0xffffffffu, tid >> 5, 0);
  uint32_t r; asm("mov.u32 %0, %%cluster_ctarank;" : "=r"(r));
  auto BAR = [&](int i) { return bars + i * 8; };
  auto FULL = [&](int s) { return bars + s * 8; };
  auto EMPTY = [&](int s) { return bars + (B_EMPTY + s) * 8; };

  int t;
  if (SMID) { unsigned smid; asm("mov.u32 %0, %%smid;" : "=r"(smid)); t = smid >> 1; }
  else { t = blockIdx.x >> 1; t = t < 4 ? t + 62 : t - 4; }
  if (SMID && (t == 60 || t == 61)) {
    if (tid == 0) {
      const int c = (t - 60) * 2 + r, t1 = clk();
      while (clk() - t1 < PFSTART) {}
      if (PF) {
#pragma unroll 1
        for (int k = 0; k < 25; k++) l2_prefetch(pt.wo + (c * 25 + k) * 4096, 8192);
#pragma unroll 1
        for (int k = 0; k < 96; k++) {
          const int kb = k >> 3;
          l2_prefetch(pt.w2 + (size_t)((k & 1) * 768 + (kb < 6 ? 2 * kb : 2 * kb - 11) * 64 + c * 16 + ((k >> 1) & 3) * 4) * S_, 16384);
        }
      }
    }
    return;
  }
  const int u7 = t - 32, q7 = (u7 * 37) >> 8;
  const int g = t < 32 ? (t & 7) : t < 60 ? 1 + u7 - 7 * q7 : 0;
  const int i = t < 32 ? (t >> 3) : t < 60 ? 4 + q7 : t - 58;
  const int qm = g * 2 + r, qj = i;

  if (EPF && warp < EPF && lane < 31) {
    const int c = qm * 8 + qj;
    const char* p = lane < 16 ? (const char*)pt.x + (c * 16 + lane) * 1280 + warp * 128 : (const char*)pt.wq + warp * 64 * 3840 + (c * 15 + lane - 16) * 128;
    asm volatile("prefetch.global.L2 [%0];" ::"l"(p));
  }
  if (elect()) {
    const int b0 = warp < 8 ? warp + 2 : warp < 10 ? warp - 8 : 76 + 2 * warp;
    mbar_init(BAR(b0), warp == 12 ? 2 : 1);
    mbar_init(BAR(b0 + (warp < 10 ? B_EMPTY : 1)), (0x4112514444444444ull >> (4 * warp)) & 15);
    asm volatile("fence.mbarrier_init.release.cluster;" ::: "memory");
    if (warp == 8) {
      mbar_expect_tx(FULL(0), 46 * KB);
      tma3d(base, &mp.x, 0, qm * 64, 0, FULL(0));
      asm volatile("prefetch.tensormap [%0];" ::"l"(&mp.wqm) : "memory");
      asm volatile("prefetch.tensormap [%0];" ::"l"(&mp.wqr) : "memory");
      sts128(BAR(LNCNT), 0, 0, 0, 0);
    }
  }
  __syncwarp();
  asm volatile("barrier.cluster.arrive.relaxed.aligned;\nbarrier.cluster.wait.aligned;" ::: "memory");
  if (warp == 8 && elect()) {
    tma3d_mc(base + 16 * KB + r * 16 * KB, &mp.wqm, qj * 80, r * 32, 0, FULL(0));
    tma3d_mc(base + 28 * KB + r * 16 * KB, &mp.wqr, qj * 80 + 64, r * 32, 0, FULL(0));
  }
  const int t0 = clk();
  const bool hasG = g < 4 || i < 7;
  const int gt = 7 * g - 21 + (g > 3) + (hasG ? i : 6), g3 = (gt * 43) >> 7;
  const int gf = g < 3 ? g * 4 + (i >> 1) : g3, gd = g < 3 ? (i & 1) : 2 + gt - 3 * g3;
  const int pm = g * 2 + (i >> 2), pn = i & 3;

  if (warp < 8) {
    asm volatile("setmaxnreg.inc.sync.aligned.u32 216;");
    const int wg = warp >> 2, w = warp & 3;
    const bool lead = (tid & 127) == 0;
    const bool keeper = (wg == (int)r);
    const int rho = lane >> 2, q = lane & 3;
    const uint32_t zero = t >> 8;
    const uint32_t dbase = (base & 0x3FFFF) >> 4, dwg = dbase + wg * (8 * KB >> 4);
    float accG[64];
    auto g_issue = [&](int n) {
      mbar_wait(FULL(NQ + n));
      TSG(0, 64 + (wg ^ (int)r) * 64 + NQ + n);
      const uint32_t o = g_off(n) >> 4;
      wg_fence();
#pragma unroll
      for (int k = 0; k < 4; k++)
        Wgmma<128, 1, 1, H128, H128>::run(accG, dwg + o + dlo(16 * KB + k * 2048, 8192), dbase + o + dlo(k * 2048, 8192), (n | k) != 0);
      wg_commit();
    };
    auto g_step = [&](int n) {
      g_issue(n);
      wg_wait<1>();
      if (lead) mbar_arrive(EMPTY(NQ + n - 1));
    };
    uint32_t Qp[10][2], Kp[10][2], Vt[10][2];
    {
      float acc[96], acr[24];
      const uint32_t rempty = mapa(EMPTY(0), r ^ 1);
#pragma unroll 1
      for (int s = 0; s < NQ; s++) {
        mbar_wait(FULL(s));
        TSG(0, 64 + (wg ^ (int)r) * 64 + s);
        const uint32_t o = q_off(s) >> 4;
        wg_fence();
#pragma unroll
        for (int k = 0; k < 4; k++) {
          Wgmma<48, 0, 1, H128, H32>::run(acr, dwg + o + dlo(k * 32, 16), dbase + o + dlo(28 * KB + (k >> 1) * 16 * KB + (k & 1) * 512, 1024), (s | k) != 0);
          Wgmma<192, 0, 1, H128, H128>::run(acc, dwg + o + dlo(k * 32, 16), dbase + o + dlo(16 * KB + (k >> 1) * 16 * KB + (k & 1) * 2048, 4096), (s | k) != 0);
        }
        wg_commit();
        wg_wait<1>();
        if (s > 0 && lead) { mbar_arrive(EMPTY(s - 1)); mbar_arrive_remote(rempty + (s - 1) * 8); }
      }
      if (ALIGN) bar_sync<1, 256>();
      g_issue(0);
      wg_wait<1>();
      reg_fence(acc); reg_fence(acr);
      if (lead) { mbar_arrive(EMPTY(NQ - 1)); mbar_arrive_remote(rempty + (NQ - 1) * 8); }
      TSG(1, 17 + (wg ^ (int)r) * 16);
#pragma unroll
      for (int c = 0; c < 10; c++) {
        const float* ak = c < 8 ? acc + 4 * (8 + c) : acr + 4 * (c - 6);
        const float* av = c < 8 ? acc + 4 * (16 + c) : acr + 4 * (c - 4);
        Kp[c][1] = pack2(ak[2], ak[3]); Vt[c][1] = movm(pack2(av[2], av[3]));
      }
      mbar_wait(EMPTY(7));
      mbar_wait(BAR(B_LNDONE));
      const uint32_t dst = base + HALO_OFF + (w == 3 ? 8 + wg : warp + 1) * 2560;
#pragma unroll
      for (int c = 0; c < 2; c++) {
        sts128(dst + c * 1280 + lane * 16, Kp[5 * c][1], Kp[5 * c + 1][1], Kp[5 * c + 3][1], Kp[5 * c + 4][1]);
        sts128(dst + c * 1280 + 512 + lane * 16, Kp[5 * c + 2][1], Vt[5 * c][1], Vt[5 * c + 1][1], Vt[5 * c + 2][1]);
        sts64(dst + c * 1280 + 1024 + lane * 8, Vt[5 * c + 3][1], Vt[5 * c + 4][1]);
      }
      bar_arrive<8, 288>();
      g_step(1);
#pragma unroll
      for (int c = 0; c < 10; c++) {
        float* aq = c < 8 ? acc + 4 * c : acr + 4 * (c - 8);
        float* ak = c < 8 ? acc + 4 * (8 + c) : acr + 4 * (c - 6);
        float* av = c < 8 ? acc + 4 * (16 + c) : acr + 4 * (c - 4);
        asm volatile("" : "+f"(aq[0]), "+f"(aq[2]), "+f"(ak[0]), "+f"(av[0])::"memory");
        Qp[c][0] = pack2(aq[0], aq[1]); Qp[c][1] = pack2(aq[2], aq[3]);
        Kp[c][0] = pack2(ak[0], ak[1]); Vt[c][0] = movm(pack2(av[0], av[1]));
      }
    }
#pragma unroll 1
    for (int n = 2; n < ATT0; n++) g_step(n);
    mbar_wait(EMPTY(NQ + 2));
    mbar_wait(BAR(B_HALO));
    {
      const bool e0 = 2 * q > rho, e1 = 2 * q + 1 > rho, first = (qm == 0 && w == 0), lo = q < 2;
      uint32_t maskE = (e0 ? 0xFFFFu : 0u) | (e1 ? 0xFFFF0000u : 0u);
      uint32_t inv0 = (first && e0) ? 0xFFFFu : 0u, inv1 = (first && e1) ? 0xFFFFu : 0u;
      const uint32_t hsrc = base + HALO_OFF + warp * 2560;
      uint32_t odst = base + OST_OFF + (warp * 16 + (lane & 15)) * 160 + (lane >> 4) * 16;
      uint32_t K0[10], V0[10], Qm[4][2];
#pragma unroll
      for (int c = 0; c < 2; c++) {
        const uint4 a = lds128(hsrc + c * 1280 + lane * 16), b = lds128(hsrc + c * 1280 + 512 + lane * 16);
        K0[5 * c] = a.x; K0[5 * c + 1] = a.y; K0[5 * c + 3] = a.z; K0[5 * c + 4] = a.w;
        K0[5 * c + 2] = b.x; V0[5 * c] = b.y; V0[5 * c + 1] = b.z; V0[5 * c + 2] = b.w;
        lds64(hsrc + c * 1280 + 1024 + lane * 8, V0[5 * c + 3], V0[5 * c + 4]);
      }
#pragma unroll
      for (int h = 0; h < 4; h++) {
        Qm[h][0] = (lo != (h & 1)) ? Qp[5 * (h >> 1) + 2][0] : 0u; Qm[h][1] = (lo != (h & 1)) ? Qp[5 * (h >> 1) + 2][1] : 0u;
        asm volatile("" : "+r"(Qm[h][0]), "+r"(Qm[h][1]));
      }
      asm volatile("" : "+r"(maskE), "+r"(inv0), "+r"(inv1), "+r"(odst));
      wg_wait<0>();
      if (lead) mbar_arrive(EMPTY(NQ + ATT0 - 1));
      mbar_wait(FULL(NQ + ATT0));
      TSG(1, 30 + (wg ^ (int)r) * 16);
      float S[4][3][4], O[4][3][4], sm[4][4];
#pragma unroll
      for (int h = 0; h < 4; h++) {
        const int G = 5 * (h >> 1) + 2, H = G - 2 + 3 * (h & 1);
        mma1688z(S[h][0], Qm[h][0], Qm[h][1], K0[G]); mma1688z(S[h][1], Qm[h][0], Qm[h][1], Kp[G][0]); mma1688z(S[h][2], Qm[h][0], Qm[h][1], Kp[G][1]);
        mma16816(S[h][0], Qp[H][0], Qp[H][1], Qp[H + 1][0], Qp[H + 1][1], K0[H], K0[H + 1]);
        mma16816(S[h][1], Qp[H][0], Qp[H][1], Qp[H + 1][0], Qp[H + 1][1], Kp[H][0], Kp[H + 1][0]);
        mma16816(S[h][2], Qp[H][0], Qp[H][1], Qp[H + 1][0], Qp[H + 1][1], Kp[H][1], Kp[H + 1][1]);
      }
#pragma unroll
      for (int h = 0; h < 4; h++) {
        uint32_t P0, P1;
        win_softmax(S[h], e0, e1, inv0, inv1, P0, P1);
        const int g0 = 5 * (h >> 1) + 2 * (h & 1);
        mma1688z(sm[h], P0, P1, 0x3F803F80u);
#pragma unroll
        for (int c = 0; c < 3; c++) mma1688z(O[h][c], P0 & maskE, 0u, V0[g0 + c]);
#pragma unroll
        for (int c = 0; c < 3; c++) mma16816(O[h][c], P0 & ~maskE, P1 & maskE, 0u, P1 & ~maskE, Vt[g0 + c][0], Vt[g0 + c][1]);
      }
#pragma unroll
      for (int hp = 0; hp < 2; hp++) {
        float (&A)[3][4] = O[2 * hp];
        float (&B)[3][4] = O[2 * hp + 1];
        const float a0 = rcp(sm[2 * hp][0]), a1 = rcp(sm[2 * hp][2]), b0 = rcp(sm[2 * hp + 1][0]), b1 = rcp(sm[2 * hp + 1][2]);
        stsm4(odst + hp * 80, pack2(A[0][0] * a0, A[0][1] * a0), pack2(A[0][2] * a1, A[0][3] * a1), pack2(A[1][0] * a0, A[1][1] * a0), pack2(A[1][2] * a1, A[1][3] * a1));
        stsm4(odst + hp * 80 + 48, pack2(B[1][0] * b0, B[1][1] * b0), pack2(B[1][2] * b1, B[1][3] * b1), pack2(B[2][0] * b0, B[2][1] * b0), pack2(B[2][2] * b1, B[2][3] * b1));
        const float c0 = lo ? a0 : b0, c1 = lo ? a1 : b1;
        stsm2(odst + hp * 80 + 32, pack2((lo ? A[2][0] : B[0][0]) * c0, (lo ? A[2][1] : B[0][1]) * c0), pack2((lo ? A[2][2] : B[0][2]) * c1, (lo ? A[2][3] : B[0][3]) * c1));
      }
      bar_sync<2, 288>();
    }
    TSG(1, 19 + (wg ^ (int)r) * 16);
#pragma unroll 1
    for (int n = ATT0; n < NG; n++) {
      const bool hold = keeper && n == NG - LEADG;
      if (hold) { wg_wait<0>(); if (lead) mbar_arrive(EMPTY(NQ + n - 1)); bar_sync<9, 256>(); }
      g_issue(n);
      if (LEADG && n == NG - 1 && !keeper) bar_arrive<9, 256>();
      wg_wait<1>();
      if (lead && !hold && n != ATT0) mbar_arrive(EMPTY(NQ + n - 1));
    }
    float4 gt0, gt1;
    {
      const float4* gp = pt.sc->gate + pm * 128 + warp * 16 + rho;
      asm volatile("ld.relaxed.gpu.global.v4.f32 {%0,%1,%2,%3}, [%4];" : "=f"(gt0.x), "=f"(gt0.y), "=f"(gt0.z), "=f"(gt0.w) : "l"(gp) : "memory");
      asm volatile("ld.relaxed.gpu.global.v4.f32 {%0,%1,%2,%3}, [%4];" : "=f"(gt1.x), "=f"(gt1.y), "=f"(gt1.z), "=f"(gt1.w) : "l"(gp + 8) : "memory");
    }
    TSG(2, 20 + (wg ^ (int)r) * 16);
    float accA[80];
    auto po_step = [&](int n, bool rel) {
      mbar_wait(FULL(SP + n));
      TSG(0, 64 + (wg ^ (int)r) * 64 + SP + n);
      const uint32_t a = dwg + (pa_off(n) >> 4), b = dbase + (pb_off(n) >> 4);
      wg_fence();
#pragma unroll
      for (int k = 0; k < 4; k++) Wgmma<160, 0, 1, H128, H64>::run(accA, a + dlo(k * 32, 16), b + dlo(k * 1024, 4096), (n | k) != 0);
      wg_commit();
      wg_wait<1>();
      if (lead && rel) mbar_arrive(EMPTY(SP + n - 1));
    };
    const int n0 = keeper ? KPO : 0;
#pragma unroll 1
    for (int n = 0; n < n0; n++) po_step(n, true);
    wg_wait<0>();
    reg_fence(accG);
    if (lead) mbar_arrive(EMPTY(SP - 1 + n0));
    TSG(2, 21 + (wg ^ (int)r) * 16);
    const uint32_t rcv = base + RECV_OFF;
    if (keeper) {
      uint32_t src = rcv + w * 2048 + lane * 16;
      uint32_t udst = rcv + (w * 16 + (lane & 15)) * 128 + (((lane >> 4) ^ (lane & 7)) << 4);
#pragma unroll 1
      for (int hf = 0; hf < 2; hf++) {
        mbar_wait(BAR(B_RECVG + hf));
        if (hf == 0) TSG(2, 22);
        uint4 v[4];
#pragma unroll
        for (int c = 0; c < 4; c++) v[c] = lds128(src + c * 512);
        __syncwarp();
#pragma unroll
        for (int c = 0; c < 4; c++) {
          const float* a = accG + 8 * c;
          auto ge = [&](float a0, float a1, uint32_t p) { return pack2(gelu_half(fmaf(a0, 0.5f, bf_lo(p))), gelu_half(fmaf(a1, 0.5f, bf_hi(p)))); };
          stsm4(udst ^ (c << 5), ge(a[0], a[1], v[c].x), ge(a[2], a[3], v[c].y), ge(a[4], a[5], v[c].z), ge(a[6], a[7], v[c].w));
        }
        asm volatile("bar.arrive %0, 160;" ::"r"(3 + hf) : "memory");
        src += 8192; udst += 8192;
#pragma unroll
        for (int e = 0; e < 32; e++) accG[e] = accG[32 + e];
      }
    } else {
      const uint32_t rdst = mapa(rcv + w * 2048 + lane * 16, r ^ 1), rbar = mapa(BAR(B_RECVG), r ^ 1), half = 0x3F003F00u;
#pragma unroll
      for (int c2 = 0; c2 < 4; c2++) {
        uint32_t bb[4];
        ldsm4(base + B1_OFF + c2 * 64 + (lane >> 3) * 16, bb[0], bb[1], bb[2], bb[3]);
#pragma unroll
        for (int cc = 0; cc < 2; cc++) {
          const float* a = accG + 16 * c2 + 8 * cc;
          const uint32_t h0 = hmul2(bb[2 * cc], half), h1 = hmul2(bb[2 * cc + 1], half);
          const uint32_t p0 = hfma2(pack2(a[0], a[1]), half, h0), p1 = hfma2(pack2(a[2], a[3]), half, h0), p2 = hfma2(pack2(a[4], a[5]), half, h1), p3 = hfma2(pack2(a[6], a[7]), half, h1);
          st_async4(rdst + (c2 >> 1) * 8192 + ((c2 & 1) * 2 + cc) * 512, p0, p1, p2, p3, rbar + (c2 >> 1) * 8);
        }

      }
    }
    TSG(2, 23 + (wg ^ (int)r) * 16);
#pragma unroll 1
    for (int n = n0; n < NPO; n++) po_step(n, n != n0);
    wg_wait<0>();
    reg_fence(accA);
    if (lead) mbar_arrive(EMPTY(SP + NPO - 1));
    sched_fence(zero);
    TSG(2, 24 + (wg ^ (int)r) * 16);
    {
      const float c0 = keeper ? gt0.z : 0.f, c1 = keeper ? gt1.z : 0.f;
#pragma unroll
      for (int e = 0; e < 80; e++) accA[e] = (e & 2) ? fmaf(gt1.x, accA[e], c1) : fmaf(gt0.x, accA[e], c0);
      reg_fence(accA);
    }
    float accY[80];
    static_assert(LEADP == 4, "send / staging buffers live in the slot of k-block NP - 5");
    {
      int sl = 0;
#pragma unroll 1
      for (int n = NPO; n < NP; n++) {
        const bool hold = keeper && n == NP - LEADP;
        if (hold) { wg_wait<0>(); if (lead) mbar_arrive(EMPTY(SP + n - 1)); bar_sync<10, 256>(); }
        mbar_wait(FULL(SP + n));
        TSG(0, 64 + (wg ^ (int)r) * 64 + SP + n);
        const uint32_t a = dwg + (pa_off(sl) >> 4), b = dbase + (pb_off(sl) >> 4);
        wg_fence();
#pragma unroll
        for (int k = 0; k < 4; k++) Wgmma<160, 1, 0, H128, H128>::run(accY, a + dlo(k * 2048, 8192), b + dlo(k * 32, 16), n != NPO || k != 0);
        wg_commit();
        if (n == NP - 1 && !keeper) bar_arrive<10, 256>();
        sl = sl == 4 ? 0 : sl + 1;
        wg_wait<1>();
        if (lead && !hold && n != NPO) mbar_arrive(EMPTY(SP + n - 1));
      }
    }
    mbar_wait(keeper ? EMPTY(NSTEP - LEADP - 1) : BAR(B_XFREE));
    TSG(3, 25 + (wg ^ (int)r) * 16);
    wg_wait<0>();
    reg_fence(accY);
    TSG(3, 26 + (wg ^ (int)r) * 16);
    auto mix = [&](int e) {
      const float om = (e & 1) ? gt1.y : gt0.y;
      return pack2(fmaf(om, accY[2 * e], accA[2 * e]), fmaf(om, accY[2 * e + 1], accA[2 * e + 1]));
    };
    const uint32_t xch = rcv + w * 1024 + lane * 16;
    const uint32_t rdst = mapa(xch, r ^ 1), rbar = mapa(BAR(B_RECVP), r ^ 1);
    const uint32_t odst = base + OUTST_OFF + (w * 16 + (lane & 15)) * 64 + (((lane >> 4) ^ ((lane >> 1) & 3)) << 4);
#pragma unroll
    for (int c = 0; c < 5; c++) {
      uint32_t pk[8];
      uint4 v0, v1;
      if (keeper) { mbar_wait(BAR(B_RECVP + c)); v0 = lds128(xch + c * 4096); v1 = lds128(xch + c * 4096 + 512); }
      if (c == 0) TSG(3, 27 + (wg ^ (int)r) * 16);
#pragma unroll
      for (int e = 0; e < 8; e++) pk[e] = mix(8 * c + e);
      if (keeper) {
        stsm4(odst + c * 4096, hadd2(pk[0], v0.x), hadd2(pk[1], v0.y), hadd2(pk[2], v0.z), hadd2(pk[3], v0.w));
        stsm4((odst ^ 32) + c * 4096, hadd2(pk[4], v1.x), hadd2(pk[5], v1.y), hadd2(pk[6], v1.z), hadd2(pk[7], v1.w));
        asm volatile("bar.arrive %0, 160;" ::"r"(11 + c) : "memory");
      } else {
        {
          st_async4(rdst + c * 4096, pk[0], pk[1], pk[2], pk[3], rbar + c * 8);
          st_async4(rdst + c * 4096 + 512, pk[4], pk[5], pk[6], pk[7], rbar + c * 8);
        }
      }
    }
    TSG(3, 28 + (wg ^ (int)r) * 16);
  } else if (warp >= 12) {
    asm volatile("setmaxnreg.dec.sync.aligned.u32 48;");
    const int lw = warp - 12;
    int row = r * 1024 + lw * 64 + g * 8 + i;
    uint2 gw[5], xn[5];
#pragma unroll
    for (int c = 0; c < 5; c++) gw[c] = ldg64((const uint2*)pt.gw + c * 32 + lane);
    const float b2v = __bfloat162float(pt.b2[row + (lane & 3) * 256]);
    if (elect()) {
#pragma unroll 1
      for (int s = NQ + lw; s < NSTEP + 5; s += 4) { mbar_init(FULL(s), 1); mbar_init(EMPTY(s), 2); }
    }
    __syncwarp();
    bar_arrive<5, 160>();
    const uint2* xp = (const uint2*)(pt.x + (size_t)row * D_) + lane;
#pragma unroll 1
    for (int k = -1; k < 5; k++, row += 256) {
      uint32_t xv[10];
#pragma unroll
      for (int c = 0; c < 5; c++) { xv[2 * c] = xn[c].x; xv[2 * c + 1] = xn[c].y; }
      if (k < 3) {
#pragma unroll
        for (int c = 0; c < 5; c++) xn[c] = ldg64(xp + c * 32);
        xp += 256 * D_ / 4;
      }
      const uint32_t st = base + (k == 0 ? HST_OFF0 : HST_OFF1 - 4 * HPITCH) + (k * 4 + lw) * HPITCH;
      if (!NOLN && (unsigned)k < 4) {
        float s0 = 0.f, s1 = 0.f, q0 = 0.f, q1 = 0.f, z0 = 0.f, z1 = 0.f;
#pragma unroll
        for (int c = 0; c < 10; c++) {
          const float lo = bf_lo(xv[c]), hi = bf_hi(xv[c]);
          const uint32_t p = hmul2(xv[c], (c & 1) ? gw[c >> 1].y : gw[c >> 1].x);
          s0 += lo; s1 += hi; q0 = fmaf(lo, lo, q0); q1 = fmaf(hi, hi, q1); z0 += bf_lo(p); z1 += bf_hi(p);
        }
        float sx = s0 + s1, sq = q0 + q1, sz = z0 + z1;
#pragma unroll
        for (int o = 1; o < 32; o <<= 1) { sx += __shfl_xor_sync(0xffffffffu, sx, o); sq += __shfl_xor_sync(0xffffffffu, sq, o); sz += __shfl_xor_sync(0xffffffffu, sz, o); }
        const float mean = sx * (1.f / D_), var = fmaxf(fmaf(-mean, mean, sq * (1.f / D_)), 0.f);
        float sd;
        asm("sqrt.approx.ftz.f32 %0, %1;" : "=f"(sd) : "f"(bf_round(bf_round(var) + 1e-5f)));
        const float rs = rcp(bf_round(sd)), rh = bf_round(rs);
        const uint32_t r1 = pack2(rh, rh), r2 = pack2(rs - rh, rs - rh), mb = pack2(mean, mean);
        const float gg = bf_round(rcp(1.f + ex2(-1.4426950408889634f * bf_round(sz)))), om = bf_round(1.f - gg);
#pragma unroll
        for (int c = 0; c < 5; c++) {
          const uint32_t a = hsub2(xv[2 * c], mb), b = hsub2(xv[2 * c + 1], mb);
          sts64(st + c * 256 + lane * 8, hfma2(a, r1, hmul2(a, r2)), hfma2(b, r1, hmul2(b, r2)));
        }
        if (lane == k) sts128(st + 1280, __float_as_uint(gg), __float_as_uint(om), __float_as_uint(om * b2v), 0);
        fence_async_smem();
        __syncwarp();
      }
      if (lane == 0) {
        if (k > 0) {
          bulk_wait0();
          unsigned old;
          asm volatile("atom.shared.inc.u32 %0, [%1], 0xffffffff;" : "=r"(old) : "r"(BAR(LNCNT) + k * 4 - 4) : "memory");
          if (old == 3) red_flag(&pt.sc->cnt[(C_H + k * 2 - 2 + r) * 32]);
          if (lw == 0) TSG(4, k == 1 ? 0 : 8);
        }
        if (!NOLN && (unsigned)k < 4) {
          bulk_st(pt.sc->h + (size_t)(row - 256) * D_, st, 1280);
          bulk_st(pt.sc->gate + row - 256, st + 1280, 16);
          bulk_commit();
        }
      }
      __syncwarp();
    }
    if (lane == 0) {
      mbar_arrive(BAR(B_LNDONE));
      if (lw == 0) {
        const int t1 = clk();
        while (!mbar_try(BAR(B_RECVP + 4))) {
          __nanosleep(100);
          if (clk() - t1 > (1 << 30)) asm volatile("st.global.u32 [%0], 0;" ::"l"(0ull) : "memory");
        }
      }
    }
  } else {
    asm volatile("setmaxnreg.dec.sync.aligned.u32 32;");
    if (warp > 8) {
      unsigned* cnt = pt.sc->cnt;
      if (warp != 10) {
        unsigned* epp = cnt + (C_EP + g * 16 + i * 2 + r) * 32;
        const unsigned ep = ld_relaxed(epp) + 1;
        const unsigned* cp = cnt + 32 * (lane < 8 ? C_H + (lane & 3) * 2 + (r ^ (lane >> 2)) : lane == 8 ? C_HALO + qm * 8 + qj : lane == 9 ? C_O + pm * 2 + r : C_U + r * 2 + lane - 10);
        const unsigned target = ep * (lane < 8 ? 64 : lane == 8 ? (qm != 0) : lane == 9 ? 4 : 60);
        const uint32_t mybar = BAR(lane < 8 ? B_HREADY + min(lane, 3) : B_HALO + lane - 8);
        unsigned todo = warp == 9 ? 0xF00 : 0xFF;
        if (warp == 9) { mbar_wait(EMPTY(7)); mbar_wait(BAR(B_LNDONE)); }
        else {
          mbar_wait(FULL(1));
          if (elect()) {
            mbar_expect_tx(BAR(B_RECVG), 8 * KB); mbar_expect_tx(BAR(B_RECVG + 1), 8 * KB);
#pragma unroll 1
            for (int k = 0; k < 9; k++) asm volatile("prefetch.tensormap [%0];" ::"l"(&mp.h + k) : "memory");
          }
          mbar_wait(EMPTY(2));
        }
#pragma unroll 1
        while (todo) {
          const unsigned act = (todo & 0xF0F) ? todo & -todo : todo;
          bool ok = false;
          if ((act >> lane) & 1) ok = (int)(ld_relaxed(cp) - target) >= 0;
          todo &= ~__ballot_sync(0xffffffffu, ok);
          if (ok) {
            asm volatile("fence.proxy.async.global;" ::: "memory");
            if (lane == 8) {
              mbar_expect_tx(mybar, 5120 + 256);
              const uint4* src = pt.sc->halo + (qm * 8 + qj) * 320;
              bulk_ld(base + HALO_OFF, src, 2560, mybar);
              bulk_ld(base + HALO_OFF + 4 * 2560, src + 160, 2560, mybar);
              bulk_ld(base + B1_OFF, pt.b1 + gf * 128, 256, mybar);
            } else {
              mbar_arrive(mybar);
            }
          }
          __syncwarp();
        }
        if (warp == 9) *epp = ep;
        else if (elect()) {
          int sl = 0, tl = t0;
#pragma unroll 1
          for (int m = 0; m < NPY; m++) {
            mbar_wait(BAR(B_UREADY + (m >= 6)));
            mbar_wait(EMPTY(SP + m));
            while (clk() - tl < USTAG) {}
            tl = clk();
            tma2d(base + pb_off(sl), &mp.uld, r * 768 + (m < 6 ? 2 * m : 2 * m - 11) * 64, pn * 160, FULL(SP + NPO + m));
            sl = sl == 4 ? 0 : sl + 1;
            TSG(5, 192 + SP + NPO + m);
          }
        }
      } else {
        if (elect()) {
          bar_sync<8, 288>(); fence_async_smem();
          bulk_st(pt.sc->halo + (qm * 8 + qj + 8) * 320, base + HALO_OFF + 8 * 2560, 5120);
          bulk_commit();
          mbar_arrive(BAR(B_HALO));
          bulk_wait0();
          red_flag(cnt + (C_HALO + qm * 8 + qj + 8) * 32);
          TSG(4, 15);
          bar_sync<2, 288>(); fence_async_smem();
          TSG(4, 7);
          tma3d_st(&mp.ost, qj * 80, qm * 64, 0, base + OST_OFF);
          bulk_commit(); bulk_wait0();
          red_flag(cnt + (C_O + qm * 2 + (qj >> 2)) * 32);
          mbar_arrive(BAR(B_OREADY));
          TSG(4, 10);
#pragma unroll 1
          for (int hf = 0; hf < 2; hf++) {
            asm volatile("bar.sync %0, 160;" ::"r"(3 + hf) : "memory");
            fence_async_smem();
            TSG(4, 11 + hf);
            if (hasG) {
              tma2d_st(&mp.ust, gf * 128 + hf * 64, gd * 128 + r * 64, base + RECV_OFF + hf * 8 * KB);
              bulk_commit(); bulk_wait0();
              red_flag(cnt + (C_U + (gf >= 6 ? 2 : 0) + hf) * 32);
            }
            TSG(4, 13 + hf);
          }
#pragma unroll 1
          for (int c = 0; c < 5; c++) mbar_expect_tx(BAR(B_RECVP + c), 4 * KB);
          mbar_arrive_remote(mapa(BAR(B_XFREE), r ^ 1));
#pragma unroll 1
          for (int c = 0; c < 5; c++) {
            asm volatile("bar.sync %0, 160;" ::"r"(11 + c) : "memory");
            fence_async_smem();
            tma2d_st(&mp.out, pn * 160 + c * 32, pm * 128 + r * 64, base + OUTST_OFF + c * 4 * KB);
          }
          bulk_commit();
          asm volatile("cp.async.bulk.wait_group.read 0;" ::: "memory");
          TSG(3, 3);
        }
      }
    } else if (elect()) {
#pragma unroll 1
      for (int s = 1; s < NQ; s++) {
        const uint32_t a = base + q_off(s), b = a + 16 * KB + r * 16 * KB;
        if (s == 4) bar_sync<5, 160>();
        if (s >= 4) mbar_wait(EMPTY(s - 4));
        else { while (clk() - t0 < s * STAGGER) {} }
        mbar_expect_tx(FULL(s), 46 * KB);
        tma3d(a, &mp.x, s * 64, qm * 64, 0, FULL(s));
        tma3d_mc(b, &mp.wqm, qj * 80, s * 64 + r * 32, 0, FULL(s));
        tma3d_mc(b + 12 * KB, &mp.wqr, qj * 80 + 64, s * 64 + r * 32, 0, FULL(s));
        TSG(5, 192 + s);
      }
      int tl = t0;
#pragma unroll 1
      for (int n = 0; n < NG; n++) {
        mbar_wait(BAR(B_HREADY + (n >> 2)));
        mbar_wait(EMPTY(n + 4 + ((0x55550156u >> (2 * n)) & 3)));
        while (clk() - tl < GSTAG) {}
        tl = clk();
        const uint32_t a = base + g_off(n);
        mbar_expect_tx(FULL(NQ + n), 32 * KB);
        tma3d(a, &mp.w1, 0, r * 1024 + n * 64, gf * 2, FULL(NQ + n));
        tma3d(a + 16 * KB, &mp.h, 0, r * 1024 + n * 64, gd * 2, FULL(NQ + n));
        TSG(5, 192 + NQ + n);
      }
      mbar_wait(BAR(B_OREADY));
      int sl = 0;
#pragma unroll 1
      for (int n = 0; n < NP; n++) {
        mbar_wait(EMPTY(n + (n < 2 ? 20 : 21)));
        if (PSTAG) { while (clk() - tl < PSTAG) {} tl = clk(); }
        mbar_expect_tx(FULL(SP + n), 36 * KB);
        if (n < NPO) {
          tma3d(base + pb_off(sl), &mp.wo, 0, r * 320 + n * 64, pn * 5, FULL(SP + n));
          tma2d(base + pa_off(sl), &mp.old_, r * 320 + n * 64, pm * 128, FULL(SP + n));
          TSG(5, 192 + SP + n);
        } else {
          tma3d(base + pa_off(sl), &mp.w2, 0, r * 768 + (n < 11 ? 2 * n - 10 : 2 * n - 21) * 64, pm * 2, FULL(SP + n));
        }
        sl = sl == 4 ? 0 : sl + 1;
      }
    }
  }
}

typedef CUresult (*EncFn)(CUtensorMap*, CUtensorMapDataType, cuuint32_t, void*, const cuuint64_t*, const cuuint64_t*, const cuuint32_t*,
                          const cuuint32_t*, CUtensorMapInterleave, CUtensorMapSwizzle, CUtensorMapL2promotion, CUtensorMapFloatOOBfill);

void mkmap(EncFn enc, CUtensorMap* m, const void* ptr, int rank, cuuint64_t d0, cuuint64_t d1, cuuint64_t d2, cuuint64_t s1, cuuint64_t s2,
           cuuint32_t b0, cuuint32_t b1, cuuint32_t b2, CUtensorMapSwizzle sw) {
  cuuint64_t dims[3] = {d0, d1, d2}, st[2] = {s1, s2};
  cuuint32_t box[3] = {b0, b1, b2}, es[3] = {1, 1, 1};
  enc(m, CU_TENSOR_MAP_DATA_TYPE_BFLOAT16, rank, (void*)ptr, dims, st, box, es, CU_TENSOR_MAP_INTERLEAVE_NONE, sw,
      CU_TENSOR_MAP_L2_PROMOTION_L2_128B, CU_TENSOR_MAP_FLOAT_OOB_FILL_NONE);
}

}

extern "C" void kernel_launch(void* const* d_in, const int* in_sizes, int n_in, void* d_out, int out_size) {
  (void)in_sizes; (void)n_in; (void)out_size;
  const __nv_bfloat16* x = (const __nv_bfloat16*)d_in[0];
  const __nv_bfloat16* wqkv = (const __nv_bfloat16*)d_in[1];
  const __nv_bfloat16* wo = (const __nv_bfloat16*)d_in[2];
  const __nv_bfloat16* w1 = (const __nv_bfloat16*)d_in[4];
  const __nv_bfloat16* w2 = (const __nv_bfloat16*)d_in[6];
  void* fn = nullptr; cudaDriverEntryPointQueryResult qr;
  cudaGetDriverEntryPoint("cuTensorMapEncodeTiled", &fn, cudaEnableDefault, &qr);
  EncFn enc = (EncFn)fn;
  void* psc;
  cudaGetSymbolAddress(&psc, g_sc);
  Scratch* sc = (Scratch*)psc;
  void *ph = sc->h, *po = sc->o, *pu = sc->u;
  const CUtensorMapSwizzle S128 = CU_TENSOR_MAP_SWIZZLE_128B, S64 = CU_TENSOR_MAP_SWIZZLE_64B, S0 = CU_TENSOR_MAP_SWIZZLE_NONE;
  Maps mp;
  mkmap(enc, &mp.x, x, 3, 640, 1024, 2, 2560, 1280, 64, 64, 2, S128);
  mkmap(enc, &mp.wqm, wqkv, 3, 640, 640, 3, 3840, 1280, 64, 32, 3, S128);
  mkmap(enc, &mp.wqr, wqkv, 3, 640, 640, 3, 3840, 1280, 16, 32, 3, CU_TENSOR_MAP_SWIZZLE_32B);
  mkmap(enc, &mp.h, ph, 3, 64, 2048, 10, 1280, 128, 64, 64, 2, S128);
  mkmap(enc, &mp.w1, w1, 3, 64, 2048, 24, 3072, 128, 64, 64, 2, S128);
  mkmap(enc, &mp.old_, po, 2, 640, 2048, 1, 1280, 0, 64, 128, 1, S128);
  mkmap(enc, &mp.wo, wo, 3, 32, 640, 20, 1280, 64, 32, 64, 5, S64);
  mkmap(enc, &mp.w2, w2, 3, 64, 1536, 32, 4096, 128, 64, 64, 2, S128);
  mkmap(enc, &mp.uld, pu, 2, 1536, 640, 1, 3072, 0, 64, 160, 1, S128);
  mkmap(enc, &mp.ost, po, 3, 640, 1024, 2, 2560, 1280, 80, 64, 2, S0);
  mkmap(enc, &mp.ust, pu, 2, 1536, 640, 1, 3072, 0, 64, 64, 1, S128);
  mkmap(enc, &mp.out, d_out, 2, 640, 2048, 1, 1280, 0, 32, 64, 1, S64);
  Ptrs pt;
  pt.w2 = w2; pt.wo = wo; pt.sc = sc; pt.x = x; pt.wq = wqkv; pt.b1 = (const __nv_bfloat16*)d_in[5]; pt.b2 = (const __nv_bfloat16*)d_in[7]; pt.gw = (const __nv_bfloat16*)d_in[8];
  int dev = 0, sms = 0;
  cudaGetDevice(&dev);
  cudaDeviceGetAttribute(&sms, cudaDevAttrMultiProcessorCount, dev);
  if (sms == 132) {
    cudaFuncSetAttribute(fused_kernel<true>, cudaFuncAttributeMaxDynamicSharedMemorySize, SMEM_BYTES);
    fused_kernel<true><<<132, 512, SMEM_BYTES, cudaStreamPerThread>>>(pt, mp);
  } else {
    cudaFuncSetAttribute(fused_kernel<false>, cudaFuncAttributeMaxDynamicSharedMemorySize, SMEM_BYTES);
    fused_kernel<false><<<128, 512, SMEM_BYTES, cudaStreamPerThread>>>(pt, mp);
  }
}
```

```cpp
#include <cuda_runtime.h>
#include <cuda_bf16.h>
#include <cuda.h>
#include <stdint.h>
#include <stddef.h>

namespace {

constexpr int S_ = 2048, D_ = 640, F_ = 1536;
constexpr int NQ = 10, NG = 16, NPO = 5, NPY = 12, SP = NQ + NG, NP = NPO + NPY, NSTEP = SP + NP;
constexpr int KB = 1024;
constexpr int OST_OFF = 160 * KB;
constexpr int RECV_OFF = 180 * KB;
constexpr int OUTST_OFF = 96 * KB;
constexpr int HALO_OFF = 200 * KB;
constexpr int HST_OFF0 = 144 * KB, HST_OFF1 = 208 * KB, HPITCH = 1280;
__host__ __device__ constexpr uint32_t hst_off(int k) { return k == 0 ? HST_OFF0 : HST_OFF1 + (k - 1) * 4 * HPITCH; }
constexpr int BAR_OFF = 225 * KB;
constexpr int B1_OFF = BAR_OFF + 1216;
constexpr int GST_OFF = B1_OFF + 128;
constexpr int SMEM_BYTES = 227 * KB;
constexpr int B_EMPTY = 48, B_HALL = 96, B_HROW0 = 97, B_LNDONE = 98, B_HALO = 100, B_OFREE = 102, B_USTAGED = 103,
              B_RECVG = 104  , B_RECVP = 147  , B_HDATA = 112, UTIME = 113  , B_XFREE = 106, B_LNROW = 107  , B_DATA = 114 - NQ  ;
#define LEADG 2
#define PF 1
#define PFSTART 5000
#define GSTAG 420
#define PSTAG 400
#define ALIGN 1
#define EPF 2
#define PST 30
#define FL 6
#define U0 2
#define WOG 20
#define PGAP 150
#define LNDELAY 1200
#define USPEC 1900
#define HG 3
#define RGAP 200
#define POG 20
#define WFENCE 0
#define USTAG 450
#define SDIV 2
#define PMAP 1
constexpr int LEADP = 4;
#define STAGGER 750
#define ATT0 8

struct Maps { CUtensorMap x, wqm, wqr, h, w1, old_, wo, w2, uld, ost, ust, out; };
struct Scratch {
  __nv_bfloat16 h[2 * S_ * D_], o[2 * S_ * D_], u[2 * D_ * F_];
  uint4 halo[2 * 136 * 320];
  float4 gate[S_];
  unsigned cnt[(4 + 4 + 32 + 136 + 128) * 32];
};
constexpr int C_H = 0, C_U = 4, C_O = 8, C_HALO = 40, C_EP = 176;
struct Ptrs { Scratch* sc; const __nv_bfloat16 *x, *wq, *gw, *b1, *b2; const __nv_bfloat16 *w2, *wo; };
__device__ __align__(1024) Scratch g_sc;
#define TSG(grp, i)

__device__ __forceinline__ uint32_t clk() { uint32_t c; asm volatile("mov.u32 %0, %%clock;" : "=r"(c)); return c; }
__device__ __forceinline__ void wait_until(uint32_t t) { while ((int)(clk() - t) < 0) {} }
template <int N, int TA, int TB, uint32_t HA, uint32_t HB> struct Wgmma;
template <int TA, int TB, uint32_t HA, uint32_t HB> struct Wgmma<48, TA, TB, HA, HB> {
  static __device__ __forceinline__ void run(float (&d)[24], uint32_t la, uint32_t lb, int sd) {
    asm volatile("{\n.reg .pred p;\n.reg .b64 da, db;\nsetp.ne.b32 p, %26, 0;\nmov.b64 da, {%24, %29};\nmov.b64 db, {%25, %30};\n"
      "wgmma.mma_async.sync.aligned.m64n48k16.f32.bf16.bf16 {%0, %1, %2, %3, %4, %5, %6, %7, %8, %9, %10, %11, %12, %13, %14, %15, %16, %17, %18, %19, %20, %21, %22, %23}, da, db, p, 1, 1, %27, %28;\n}\n"
      : "+f"(d[0]), "+f"(d[1]), "+f"(d[2]), "+f"(d[3]), "+f"(d[4]), "+f"(d[5]), "+f"(d[6]), "+f"(d[7]), "+f"(d[8]), "+f"(d[9]), "+f"(d[10]), "+f"(d[11]), "+f"(d[12]), "+f"(d[13]), "+f"(d[14]), "+f"(d[15]), "+f"(d[16]), "+f"(d[17]), "+f"(d[18]), "+f"(d[19]), "+f"(d[20]), "+f"(d[21]), "+f"(d[22]), "+f"(d[23])
      : "r"(la), "r"(lb), "r"(sd), "n"(TA), "n"(TB), "n"(HA), "n"(HB));
  }
};
template <int TA, int TB, uint32_t HA, uint32_t HB> struct Wgmma<64, TA, TB, HA, HB> {
  static __device__ __forceinline__ void run(float (&d)[32], uint32_t la, uint32_t lb, int sd) {
    asm volatile("{\n.reg .pred p;\n.reg .b64 da, db;\nsetp.ne.b32 p, %34, 0;\nmov.b64 da, {%32, %37};\nmov.b64 db, {%33, %38};\n"
      "wgmma.mma_async.sync.aligned.m64n64k16.f32.bf16.bf16 {%0, %1, %2, %3, %4, %5, %6, %7, %8, %9, %10, %11, %12, %13, %14, %15, %16, %17, %18, %19, %20, %21, %22, %23, %24, %25, %26, %27, %28, %29, %30, %31}, da, db, p, 1, 1, %35, %36;\n}\n"
      : "+f"(d[0]), "+f"(d[1]), "+f"(d[2]), "+f"(d[3]), "+f"(d[4]), "+f"(d[5]), "+f"(d[6]), "+f"(d[7]), "+f"(d[8]), "+f"(d[9]), "+f"(d[10]), "+f"(d[11]), "+f"(d[12]), "+f"(d[13]), "+f"(d[14]), "+f"(d[15]), "+f"(d[16]), "+f"(d[17]), "+f"(d[18]), "+f"(d[19]), "+f"(d[20]), "+f"(d[21]), "+f"(d[22]), "+f"(d[23]), "+f"(d[24]), "+f"(d[25]), "+f"(d[26]), "+f"(d[27]), "+f"(d[28]), "+f"(d[29]), "+f"(d[30]), "+f"(d[31])
      : "r"(la), "r"(lb), "r"(sd), "n"(TA), "n"(TB), "n"(HA), "n"(HB));
  }
};
template <int TA, int TB, uint32_t HA, uint32_t HB> struct Wgmma<128, TA, TB, HA, HB> {
  static __device__ __forceinline__ void run(float (&d)[64], uint32_t la, uint32_t lb, int sd) {
    asm volatile("{\n.reg .pred p;\n.reg .b64 da, db;\nsetp.ne.b32 p, %66, 0;\nmov.b64 da, {%64, %69};\nmov.b64 db, {%65, %70};\n"
      "wgmma.mma_async.sync.aligned.m64n128k16.f32.bf16.bf16 {%0, %1, %2, %3, %4, %5, %6, %7, %8, %9, %10, %11, %12, %13, %14, %15, %16, %17, %18, %19, %20, %21, %22, %23, %24, %25, %26, %27, %28, %29, %30, %31, %32, %33, %34, %35, %36, %37, %38, %39, %40, %41, %42, %43, %44, %45, %46, %47, %48, %49, %50, %51, %52, %53, %54, %55, %56, %57, %58, %59, %60, %61, %62, %63}, da, db, p, 1, 1, %67, %68;\n}\n"
      : "+f"(d[0]), "+f"(d[1]), "+f"(d[2]), "+f"(d[3]), "+f"(d[4]), "+f"(d[5]), "+f"(d[6]), "+f"(d[7]), "+f"(d[8]), "+f"(d[9]), "+f"(d[10]), "+f"(d[11]), "+f"(d[12]), "+f"(d[13]), "+f"(d[14]), "+f"(d[15]), "+f"(d[16]), "+f"(d[17]), "+f"(d[18]), "+f"(d[19]), "+f"(d[20]), "+f"(d[21]), "+f"(d[22]), "+f"(d[23]), "+f"(d[24]), "+f"(d[25]), "+f"(d[26]), "+f"(d[27]), "+f"(d[28]), "+f"(d[29]), "+f"(d[30]), "+f"(d[31]), "+f"(d[32]), "+f"(d[33]), "+f"(d[34]), "+f"(d[35]), "+f"(d[36]), "+f"(d[37]), "+f"(d[38]), "+f"(d[39]), "+f"(d[40]), "+f"(d[41]), "+f"(d[42]), "+f"(d[43]), "+f"(d[44]), "+f"(d[45]), "+f"(d[46]), "+f"(d[47]), "+f"(d[48]), "+f"(d[49]), "+f"(d[50]), "+f"(d[51]), "+f"(d[52]), "+f"(d[53]), "+f"(d[54]), "+f"(d[55]), "+f"(d[56]), "+f"(d[57]), "+f"(d[58]), "+f"(d[59]), "+f"(d[60]), "+f"(d[61]), "+f"(d[62]), "+f"(d[63])
      : "r"(la), "r"(lb), "r"(sd), "n"(TA), "n"(TB), "n"(HA), "n"(HB));
  }
};
template <int TA, int TB, uint32_t HA, uint32_t HB> struct Wgmma<160, TA, TB, HA, HB> {
  static __device__ __forceinline__ void run(float (&d)[80], uint32_t la, uint32_t lb, int sd) {
    asm volatile("{\n.reg .pred p;\n.reg .b64 da, db;\nsetp.ne.b32 p, %82, 0;\nmov.b64 da, {%80, %85};\nmov.b64 db, {%81, %86};\n"
      "wgmma.mma_async.sync.aligned.m64n160k16.f32.bf16.bf16 {%0, %1, %2, %3, %4, %5, %6, %7, %8, %9, %10, %11, %12, %13, %14, %15, %16, %17, %18, %19, %20, %21, %22, %23, %24, %25, %26, %27, %28, %29, %30, %31, %32, %33, %34, %35, %36, %37, %38, %39, %40, %41, %42, %43, %44, %45, %46, %47, %48, %49, %50, %51, %52, %53, %54, %55, %56, %57, %58, %59, %60, %61, %62, %63, %64, %65, %66, %67, %68, %69, %70, %71, %72, %73, %74, %75, %76, %77, %78, %79}, da, db, p, 1, 1, %83, %84;\n}\n"
      : "+f"(d[0]), "+f"(d[1]), "+f"(d[2]), "+f"(d[3]), "+f"(d[4]), "+f"(d[5]), "+f"(d[6]), "+f"(d[7]), "+f"(d[8]), "+f"(d[9]), "+f"(d[10]), "+f"(d[11]), "+f"(d[12]), "+f"(d[13]), "+f"(d[14]), "+f"(d[15]), "+f"(d[16]), "+f"(d[17]), "+f"(d[18]), "+f"(d[19]), "+f"(d[20]), "+f"(d[21]), "+f"(d[22]), "+f"(d[23]), "+f"(d[24]), "+f"(d[25]), "+f"(d[26]), "+f"(d[27]), "+f"(d[28]), "+f"(d[29]), "+f"(d[30]), "+f"(d[31]), "+f"(d[32]), "+f"(d[33]), "+f"(d[34]), "+f"(d[35]), "+f"(d[36]), "+f"(d[37]), "+f"(d[38]), "+f"(d[39]), "+f"(d[40]), "+f"(d[41]), "+f"(d[42]), "+f"(d[43]), "+f"(d[44]), "+f"(d[45]), "+f"(d[46]), "+f"(d[47]), "+f"(d[48]), "+f"(d[49]), "+f"(d[50]), "+f"(d[51]), "+f"(d[52]), "+f"(d[53]), "+f"(d[54]), "+f"(d[55]), "+f"(d[56]), "+f"(d[57]), "+f"(d[58]), "+f"(d[59]), "+f"(d[60]), "+f"(d[61]), "+f"(d[62]), "+f"(d[63]), "+f"(d[64]), "+f"(d[65]), "+f"(d[66]), "+f"(d[67]), "+f"(d[68]), "+f"(d[69]), "+f"(d[70]), "+f"(d[71]), "+f"(d[72]), "+f"(d[73]), "+f"(d[74]), "+f"(d[75]), "+f"(d[76]), "+f"(d[77]), "+f"(d[78]), "+f"(d[79])
      : "r"(la), "r"(lb), "r"(sd), "n"(TA), "n"(TB), "n"(HA), "n"(HB));
  }
};
template <int TA, int TB, uint32_t HA, uint32_t HB> struct Wgmma<192, TA, TB, HA, HB> {
  static __device__ __forceinline__ void run(float (&d)[96], uint32_t la, uint32_t lb, int sd) {
    asm volatile("{\n.reg .pred p;\n.reg .b64 da, db;\nsetp.ne.b32 p, %98, 0;\nmov.b64 da, {%96, %101};\nmov.b64 db, {%97, %102};\n"
      "wgmma.mma_async.sync.aligned.m64n192k16.f32.bf16.bf16 {%0, %1, %2, %3, %4, %5, %6, %7, %8, %9, %10, %11, %12, %13, %14, %15, %16, %17, %18, %19, %20, %21, %22, %23, %24, %25, %26, %27, %28, %29, %30, %31, %32, %33, %34, %35, %36, %37, %38, %39, %40, %41, %42, %43, %44, %45, %46, %47, %48, %49, %50, %51, %52, %53, %54, %55, %56, %57, %58, %59, %60, %61, %62, %63, %64, %65, %66, %67, %68, %69, %70, %71, %72, %73, %74, %75, %76, %77, %78, %79, %80, %81, %82, %83, %84, %85, %86, %87, %88, %89, %90, %91, %92, %93, %94, %95}, da, db, p, 1, 1, %99, %100;\n}\n"
      : "+f"(d[0]), "+f"(d[1]), "+f"(d[2]), "+f"(d[3]), "+f"(d[4]), "+f"(d[5]), "+f"(d[6]), "+f"(d[7]), "+f"(d[8]), "+f"(d[9]), "+f"(d[10]), "+f"(d[11]), "+f"(d[12]), "+f"(d[13]), "+f"(d[14]), "+f"(d[15]), "+f"(d[16]), "+f"(d[17]), "+f"(d[18]), "+f"(d[19]), "+f"(d[20]), "+f"(d[21]), "+f"(d[22]), "+f"(d[23]), "+f"(d[24]), "+f"(d[25]), "+f"(d[26]), "+f"(d[27]), "+f"(d[28]), "+f"(d[29]), "+f"(d[30]), "+f"(d[31]), "+f"(d[32]), "+f"(d[33]), "+f"(d[34]), "+f"(d[35]), "+f"(d[36]), "+f"(d[37]), "+f"(d[38]), "+f"(d[39]), "+f"(d[40]), "+f"(d[41]), "+f"(d[42]), "+f"(d[43]), "+f"(d[44]), "+f"(d[45]), "+f"(d[46]), "+f"(d[47]), "+f"(d[48]), "+f"(d[49]), "+f"(d[50]), "+f"(d[51]), "+f"(d[52]), "+f"(d[53]), "+f"(d[54]), "+f"(d[55]), "+f"(d[56]), "+f"(d[57]), "+f"(d[58]), "+f"(d[59]), "+f"(d[60]), "+f"(d[61]), "+f"(d[62]), "+f"(d[63]), "+f"(d[64]), "+f"(d[65]), "+f"(d[66]), "+f"(d[67]), "+f"(d[68]), "+f"(d[69]), "+f"(d[70]), "+f"(d[71]), "+f"(d[72]), "+f"(d[73]), "+f"(d[74]), "+f"(d[75]), "+f"(d[76]), "+f"(d[77]), "+f"(d[78]), "+f"(d[79]), "+f"(d[80]), "+f"(d[81]), "+f"(d[82]), "+f"(d[83]), "+f"(d[84]), "+f"(d[85]), "+f"(d[86]), "+f"(d[87]), "+f"(d[88]), "+f"(d[89]), "+f"(d[90]), "+f"(d[91]), "+f"(d[92]), "+f"(d[93]), "+f"(d[94]), "+f"(d[95])
      : "r"(la), "r"(lb), "r"(sd), "n"(TA), "n"(TB), "n"(HA), "n"(HB));
  }
};

__device__ __forceinline__ uint32_t smem_u32(const void* p) { return (uint32_t)__cvta_generic_to_shared(p); }
__device__ __forceinline__ void mbar_init(uint32_t bar, int cnt) { asm volatile("mbarrier.init.shared::cta.b64 [%0], %1;" ::"r"(bar), "r"(cnt) : "memory"); }
__device__ __forceinline__ void mbar_expect_tx(uint32_t bar, uint32_t bytes) { asm volatile("mbarrier.arrive.expect_tx.shared::cta.b64 _, [%0], %1;" ::"r"(bar), "r"(bytes) : "memory"); }
__device__ __forceinline__ void mbar_arrive(uint32_t bar) { asm volatile("mbarrier.arrive.shared::cta.b64 _, [%0];" ::"r"(bar) : "memory"); }
__device__ __forceinline__ uint32_t mapa(uint32_t a, uint32_t cta) { uint32_t r; asm("mapa.shared::cluster.u32 %0, %1, %2;" : "=r"(r) : "r"(a), "r"(cta)); return r; }
__device__ __forceinline__ void mbar_arrive_remote(uint32_t rbar) { asm volatile("mbarrier.arrive.shared::cluster.b64 _, [%0];" ::"r"(rbar) : "memory"); }
__device__ __forceinline__ void mbar_wait(uint32_t bar) {
  asm volatile("{\n.reg .pred p;\nW_LOOP:\nmbarrier.try_wait.parity.shared::cta.b64 p, [%0], 0;\n@!p bra.uni W_LOOP;\n}" ::"r"(bar) : "memory");
}
__device__ __forceinline__ void mbar_wait_par(uint32_t bar, uint32_t par) {
  asm volatile("{\n.reg .pred p;\nC_LOOP:\nmbarrier.try_wait.parity.shared::cta.b64 p, [%0], %1;\n@!p bra.uni C_LOOP;\n}" ::"r"(bar), "r"(par) : "memory");
}
__device__ __forceinline__ uint32_t lds32(uint32_t a) { uint32_t v; asm volatile("ld.shared.u32 %0, [%1];" : "=r"(v) : "r"(a) : "memory"); return v; }
__device__ __forceinline__ bool mbar_try(uint32_t bar) {
  uint32_t ok;
  asm volatile("{\n.reg .pred p;\nmbarrier.test_wait.parity.shared::cta.b64 p, [%1], 0;\nselp.b32 %0, 1, 0, p;\n}" : "=r"(ok) : "r"(bar) : "memory");
  return ok;
}
__device__ __forceinline__ bool elect() {
  uint32_t ok;
  asm volatile("{\n.reg .pred p;\nelect.sync _|p, 0xffffffff;\nselp.b32 %0, 1, 0, p;\n}" : "=r"(ok));
  return ok;
}
__device__ __forceinline__ void tma2d(uint32_t dst, const CUtensorMap* m, int c0, int c1, uint32_t bar) {
  asm volatile("cp.async.bulk.tensor.2d.shared::cluster.global.mbarrier::complete_tx::bytes [%0], [%1, {%3,%4}], [%2];" ::"r"(dst), "l"(m), "r"(bar), "r"(c0), "r"(c1) : "memory");
}
__device__ __forceinline__ void tma3d(uint32_t dst, const CUtensorMap* m, int c0, int c1, int c2, uint32_t bar) {
  asm volatile("cp.async.bulk.tensor.3d.shared::cluster.global.mbarrier::complete_tx::bytes [%0], [%1, {%3,%4,%5}], [%2];" ::"r"(dst), "l"(m), "r"(bar), "r"(c0), "r"(c1), "r"(c2) : "memory");
}
__device__ __forceinline__ void tma3d_mc(uint32_t dst, const CUtensorMap* m, int c0, int c1, int c2, uint32_t bar) {
  asm volatile("cp.async.bulk.tensor.3d.shared::cluster.global.mbarrier::complete_tx::bytes.multicast::cluster [%0], [%1, {%3,%4,%5}], [%2], %6;" ::"r"(dst), "l"(m), "r"(bar), "r"(c0), "r"(c1), "r"(c2), "h"((uint16_t)3) : "memory");
}
__device__ __forceinline__ void tma2d_st(const CUtensorMap* m, int c0, int c1, uint32_t src) {
  asm volatile("cp.async.bulk.tensor.2d.global.shared::cta.bulk_group [%0, {%2,%3}], [%1];" ::"l"(m), "r"(src), "r"(c0), "r"(c1) : "memory");
}
__device__ __forceinline__ void tma3d_st(const CUtensorMap* m, int c0, int c1, int c2, uint32_t src) {
  asm volatile("cp.async.bulk.tensor.3d.global.shared::cta.bulk_group [%0, {%2,%3,%4}], [%1];" ::"l"(m), "r"(src), "r"(c0), "r"(c1), "r"(c2) : "memory");
}
__device__ __forceinline__ void bulk_commit() { asm volatile("cp.async.bulk.commit_group;" ::: "memory"); }
__device__ __forceinline__ void bulk_wait0() { asm volatile("cp.async.bulk.wait_group 0;" ::: "memory"); }
__device__ __forceinline__ void fence_async_smem() { asm volatile("fence.proxy.async.shared::cta;" ::: "memory"); }
__device__ __forceinline__ void wg_fence() { asm volatile("wgmma.fence.sync.aligned;" ::: "memory"); }
__device__ __forceinline__ void wg_commit() { asm volatile("wgmma.commit_group.sync.aligned;" ::: "memory"); }
template <int N> __device__ __forceinline__ void wg_wait() { asm volatile("wgmma.wait_group.sync.aligned %0;" ::"n"(N) : "memory"); }
template <int N> __device__ __forceinline__ void reg_fence(float (&a)[N]) {
#pragma unroll
  for (int i = 0; i < N; i++) asm volatile("" : "+f"(a[i])::"memory");
}
template <int ID, int N> __device__ __forceinline__ void bar_sync() { asm volatile("bar.sync %0, %1;" ::"n"(ID), "n"(N) : "memory"); }
template <int ID, int N> __device__ __forceinline__ void bar_arrive() { asm volatile("bar.arrive %0, %1;" ::"n"(ID), "n"(N) : "memory"); }
__host__ __device__ constexpr uint32_t dlo(uint32_t off, uint32_t lbo) { return (off >> 4) | ((lbo >> 4) << 16); }
__host__ __device__ constexpr uint32_t dhi(uint32_t sbo, uint32_t swz) { return (sbo >> 4) | (swz << 30); }
constexpr uint32_t H128 = dhi(1024, 1), H64 = dhi(512, 2), H32 = dhi(256, 3);
__device__ __forceinline__ uint32_t pack2(float lo, float hi) { uint32_t r; asm("cvt.rn.bf16x2.f32 %0, %1, %2;" : "=r"(r) : "f"(hi), "f"(lo)); return r; }
__device__ __forceinline__ float bf_lo(uint32_t v) { return __uint_as_float(v << 16); }
__device__ __forceinline__ float bf_hi(uint32_t v) { return __uint_as_float(v & 0xFFFF0000u); }
__device__ __forceinline__ float bf_round(float v) { return __bfloat162float(__float2bfloat16_rn(v)); }
__device__ __forceinline__ uint32_t movm(uint32_t a) { uint32_t d; asm volatile("movmatrix.sync.aligned.m8n8.trans.b16 %0, %1;" : "=r"(d) : "r"(a)); return d; }
__device__ __forceinline__ void stsm4(uint32_t addr, uint32_t a, uint32_t b, uint32_t c, uint32_t d) {
  asm volatile("stmatrix.sync.aligned.m8n8.x4.shared.b16 [%0], {%1,%2,%3,%4};" ::"r"(addr), "r"(a), "r"(b), "r"(c), "r"(d) : "memory");
}
__device__ __forceinline__ void stsm2(uint32_t addr, uint32_t a, uint32_t b) {
  asm volatile("stmatrix.sync.aligned.m8n8.x2.shared.b16 [%0], {%1,%2};" ::"r"(addr), "r"(a), "r"(b) : "memory");
}
__device__ __forceinline__ void sts128(uint32_t addr, uint32_t a, uint32_t b, uint32_t c, uint32_t d) {
  asm volatile("st.shared.v4.b32 [%0], {%1,%2,%3,%4};" ::"r"(addr), "r"(a), "r"(b), "r"(c), "r"(d) : "memory");
}
__device__ __forceinline__ void sts64(uint32_t addr, uint32_t a, uint32_t b) { asm volatile("st.shared.v2.b32 [%0], {%1,%2};" ::"r"(addr), "r"(a), "r"(b) : "memory"); }
__device__ __forceinline__ uint4 lds128(uint32_t addr) { uint4 v; asm volatile("ld.shared.v4.b32 {%0,%1,%2,%3}, [%4];" : "=r"(v.x), "=r"(v.y), "=r"(v.z), "=r"(v.w) : "r"(addr) : "memory"); return v; }
__device__ __forceinline__ uint32_t hmul2(uint32_t a, uint32_t b) { uint32_t d; asm("mul.rn.bf16x2 %0, %1, %2;" : "=r"(d) : "r"(a), "r"(b)); return d; }
__device__ __forceinline__ uint32_t hsub2(uint32_t a, uint32_t b) { uint32_t d; asm("sub.rn.bf16x2 %0, %1, %2;" : "=r"(d) : "r"(a), "r"(b)); return d; }
__device__ __forceinline__ void mma16816(float (&c)[4], uint32_t a0, uint32_t a1, uint32_t a2, uint32_t a3, uint32_t b0, uint32_t b1) {
  asm volatile("mma.sync.aligned.m16n8k16.row.col.f32.bf16.bf16.f32 {%0,%1,%2,%3}, {%4,%5,%6,%7}, {%8,%9}, {%0,%1,%2,%3};"
               : "+f"(c[0]), "+f"(c[1]), "+f"(c[2]), "+f"(c[3]) : "r"(a0), "r"(a1), "r"(a2), "r"(a3), "r"(b0), "r"(b1));
}
__device__ __forceinline__ void mma1688z(float (&c)[4], uint32_t a0, uint32_t a1, uint32_t b0) {
  asm volatile("mma.sync.aligned.m16n8k8.row.col.f32.bf16.bf16.f32 {%0,%1,%2,%3}, {%4,%5}, {%6}, {%7,%7,%7,%7};"
               : "=f"(c[0]), "=f"(c[1]), "=f"(c[2]), "=f"(c[3]) : "r"(a0), "r"(a1), "r"(b0), "f"(0.f));
}
__device__ __forceinline__ unsigned ld_relaxed(const unsigned* p) { unsigned v; asm volatile("ld.relaxed.gpu.global.u32 %0, [%1];" : "=r"(v) : "l"(p) : "memory"); return v; }
__device__ __forceinline__ unsigned ld_acquire(const unsigned* p) { unsigned v; asm volatile("ld.acquire.gpu.global.u32 %0, [%1];" : "=r"(v) : "l"(p) : "memory"); return v; }
__device__ __forceinline__ void hint(unsigned* p) { asm volatile("red.relaxed.gpu.global.add.u32 [%0], 1;" ::"l"(p) : "memory"); }
__device__ __forceinline__ void await(const unsigned* p, unsigned target) { while ((int)(ld_relaxed(p) - target) < 0) {} }
__device__ __forceinline__ void bulk_st(void* g, uint32_t src, uint32_t bytes) {
  asm volatile("cp.async.bulk.global.shared::cta.bulk_group [%0], [%1], %2;" ::"l"(g), "r"(src), "r"(bytes) : "memory");
}
__device__ __forceinline__ void bulk_ld(uint32_t dst, const void* g, uint32_t bytes, uint32_t bar) {
  asm volatile("cp.async.bulk.shared::cluster.global.mbarrier::complete_tx::bytes [%0], [%1], %2, [%3];" ::"r"(dst), "l"(g), "r"(bytes), "r"(bar) : "memory");
}
__device__ __forceinline__ uint2 ldg64(const uint2* p) { uint2 v; asm volatile("ld.global.nc.v2.u32 {%0,%1}, [%2];" : "=r"(v.x), "=r"(v.y) : "l"(p)); return v; }
__device__ __forceinline__ void st_async4(uint32_t raddr, uint32_t a, uint32_t b, uint32_t c, uint32_t d, uint32_t rbar) {
  asm volatile("st.async.weak.shared::cluster.mbarrier::complete_tx::bytes.v4.b32 [%0], {%1,%2,%3,%4}, [%5];" ::"r"(raddr), "r"(a), "r"(b), "r"(c), "r"(d), "r"(rbar) : "memory");
}
__device__ __forceinline__ void lds64(uint32_t addr, uint32_t& a, uint32_t& b) { asm volatile("ld.shared.v2.b32 {%0,%1}, [%2];" : "=r"(a), "=r"(b) : "r"(addr) : "memory"); }
__device__ __forceinline__ void l2_prefetch(const void* g, uint32_t bytes) { asm volatile("cp.async.bulk.prefetch.L2.global [%0], %1;" ::"l"(g), "r"(bytes) : "memory"); }
__device__ __forceinline__ uint32_t hadd2(uint32_t a, uint32_t b) { uint32_t d; asm("add.rn.bf16x2 %0, %1, %2;" : "=r"(d) : "r"(a), "r"(b)); return d; }
__device__ __forceinline__ uint32_t hfma2(uint32_t a, uint32_t b, uint32_t c) { uint32_t d; asm("fma.rn.bf16x2 %0, %1, %2, %3;" : "=r"(d) : "r"(a), "r"(b), "r"(c)); return d; }
__device__ __forceinline__ uint32_t hmax2(uint32_t a, uint32_t b) { uint32_t d; asm("max.bf16x2 %0, %1, %2;" : "=r"(d) : "r"(a), "r"(b)); return d; }
__device__ __forceinline__ float rcp(float x) { float y; asm("rcp.approx.ftz.f32 %0, %1;" : "=f"(y) : "f"(x)); return y; }
__device__ __forceinline__ float ex2(float x) { float y; asm("ex2.approx.ftz.f32 %0, %1;" : "=f"(y) : "f"(x)); return y; }
__device__ __forceinline__ float gelu_half(float y) {
  float z = y * fmaf(y * y, 8.f * 0.044715f * 0.7978845608028654f, 2.f * 0.7978845608028654f), t;
  asm("tanh.approx.f32 %0, %1;" : "=f"(t) : "f"(z));
  return fmaf(y, t, y);
}
__device__ __forceinline__ void ldsm4(uint32_t addr, uint32_t& a, uint32_t& b, uint32_t& c, uint32_t& d) {
  asm volatile("ldmatrix.sync.aligned.m8n8.x4.shared.b16 {%0,%1,%2,%3}, [%4];" : "=r"(a), "=r"(b), "=r"(c), "=r"(d) : "r"(addr) : "memory");
}

__host__ __device__ constexpr uint32_t q_off(int s) { return ((0xA630u >> (4 * (s & 3))) & 15) * 16 * KB; }
__host__ __device__ constexpr uint32_t g_off(int n) { return (uint32_t)((0x2103421034210534ull >> (4 * n)) & 15) * 32 * KB; }
__host__ __device__ constexpr uint32_t pa_off(int sl) { return (uint32_t)((0x0E05182029ull >> (8 * sl)) & 255) * 4 * KB; }
__host__ __device__ constexpr uint32_t pb_off(int sl) { return (uint32_t)((0x1209002432ull >> (8 * sl)) & 255) * 4 * KB; }

__device__ __forceinline__ void win_softmax(const float (&S)[3][4], bool e0, bool e1, uint32_t inv0, uint32_t inv1, uint32_t& P0, uint32_t& P1) {
  const uint32_t NEG = 0xCF85u;
  const float L2E = 0.22360679774997896f * 1.4426950408889634f;
  uint32_t A = pack2(e0 ? S[0][0] : S[1][0], e0 ? S[1][2] : S[2][2]);
  uint32_t B = pack2(e1 ? S[0][1] : S[1][1], e1 ? S[1][3] : S[2][3]);
  A = (A & ~inv0) | (NEG & inv0); B = (B & ~inv1) | (NEG & inv1);
  uint32_t m = hmax2(A, B);
  m = hmax2(m, __shfl_xor_sync(0xffffffffu, m, 1));
  m = hmax2(m, __shfl_xor_sync(0xffffffffu, m, 2));
  const float m0 = -bf_lo(m) * L2E, m1 = -bf_hi(m) * L2E;
  P0 = pack2(ex2(fmaf(bf_lo(A), L2E, m0)), ex2(fmaf(bf_lo(B), L2E, m0)));
  P1 = pack2(ex2(fmaf(bf_hi(A), L2E, m1)), ex2(fmaf(bf_hi(B), L2E, m1)));
}

template <bool SMID>
__global__ void __cluster_dims__(2, 1, 1) __launch_bounds__(512, 1)
fused_kernel(const Ptrs pt, const __grid_constant__ Maps mp) {
  extern __shared__ __align__(1024) uint8_t smem_raw[];
  const uint32_t base = smem_u32(smem_raw);
  const uint32_t bars = base + BAR_OFF;
  const int tid = threadIdx.x, lane = tid & 31;
  const int warp = __shfl_sync(0xffffffffu, tid >> 5, 0);
  uint32_t r; asm("mov.u32 %0, %%cluster_ctarank;" : "=r"(r));
  auto BAR = [&](int i) { return bars + i * 8; };
  auto FULL = [&](int s) { return bars + s * 8; };
  auto EMPTY = [&](int s) { return bars + (B_EMPTY + s) * 8; };
  auto DATA = [&](int s) { return bars + (B_DATA + s) * 8; };

  int t;
  if (SMID) { unsigned smid; asm("mov.u32 %0, %%smid;" : "=r"(smid)); t = smid >> 1; }
  else { t = blockIdx.x >> 1; t = t < 4 ? t + 62 : t - 4; }
  if (SMID && (t == 60 || t == 61)) {
    if (tid == 0) {
      const int c = (t - 60) * 2 + r;
      const uint32_t t1 = clk();
      wait_until(t1 + PFSTART);
      if (PF) {
#pragma unroll 1
        for (int k = 0; k < 25; k++) l2_prefetch(pt.wo + (c * 25 + k) * 4096, 8192);
#pragma unroll 1
        for (int k = 0; k < 96; k++) {
          const int kb = k >> 3;
          l2_prefetch(pt.w2 + (size_t)((k & 1) * 768 + kb * 64 + c * 16 + ((k >> 1) & 3) * 4) * S_, 16384);
        }
      }
    }
    return;
  }
  const int u7 = t - 32, q7 = (u7 * 37) >> 8;
  const int g = t < 32 ? (t & 7) : t < 60 ? 1 + u7 - 7 * q7 : 0;
  const int i = t < 32 ? (t >> 3) : t < 60 ? 4 + q7 : t - 58;
  const int qm = g * 2 + r, qj = i;

  auto early_pf = [&]() {
    const int c = qm * 8 + qj;
    const char* p = lane < 16 ? (const char*)pt.x + (c * 16 + lane) * 1280 + warp * 128 : (const char*)pt.wq + warp * 64 * 3840 + (c * 15 + lane - 16) * 128;
    if (lane < 31) asm volatile("prefetch.global.L2 [%0];" ::"l"(p));
  };
  if (EPF && warp == 0) early_pf();
  if (elect()) {
    const int b0 = warp < 8 ? warp + 2 : warp < 10 ? warp - 8 : 76 + 2 * warp;
    if (warp > 12) mbar_init(BAR(95 + warp), 4);
    mbar_init(BAR(b0), warp == 12 ? 2 : 1);
    mbar_init(BAR(b0 + (warp < 10 ? B_EMPTY : 1)), (0x4112114444444444ull >> (4 * warp)) & 15);
    asm volatile("fence.mbarrier_init.release.cluster;" ::: "memory");
  }
  __syncwarp();
  asm volatile("barrier.cluster.arrive.relaxed.aligned;" ::: "memory");
  if (warp == 8) {
    if (elect()) {
      mbar_expect_tx(FULL(0), 46 * KB);
      tma3d(base, &mp.x, 0, qm * 64, 0, FULL(0));
      asm volatile("prefetch.tensormap [%0];" ::"l"(&mp.wqm) : "memory");
      asm volatile("prefetch.tensormap [%0];" ::"l"(&mp.wqr) : "memory");
    }
    __syncwarp();
  }
  asm volatile("barrier.cluster.wait.aligned;" ::: "memory");
  if (warp == 8 && elect()) {
    tma3d_mc(base + 16 * KB + r * 16 * KB, &mp.wqm, qj * 80, r * 32, 0, FULL(0));
    tma3d_mc(base + 28 * KB + r * 16 * KB, &mp.wqr, qj * 80 + 64, r * 32, 0, FULL(0));
  }
  const uint32_t t0 = clk();
  const bool hasG = g < 4 || i < 7;
  const int gt = 7 * g - 21 + (g > 3) + (hasG ? i : 6), g3 = (gt * 43) >> 7;
  const int gf = g < 3 ? g * 4 + (i >> 1) : g3, gd = g < 3 ? (i & 1) : 2 + gt - 3 * g3;
  const int pm = g * 2 + (i >> 2), pn = i & 3;

  unsigned* const epp = pt.sc->cnt + (C_EP + g * 16 + i * 2 + r) * 32;
  auto dep_load = [&](int n, int sl, int par) {
    const bool po = n < NPO;
    mbar_expect_tx(DATA(SP + n), po ? 16 * KB : 20 * KB);
    tma2d(base + (po ? pa_off(sl) : pb_off(sl)), po ? &mp.old_ : &mp.uld, (po ? r * 320 : r * 768 - NPO * 64) + n * 64, po ? pm * 128 + par * S_ : pn * 160 + par * D_, DATA(SP + n));
  };
  auto h_load = [&](int n, int par) {
    mbar_expect_tx(DATA(NQ + n), 16 * KB);
    tma3d(base + g_off(n) + 16 * KB, &mp.h, 0, par * S_ + r * 1024 + n * 64, gd * 2, DATA(NQ + n));
  };

  if (warp < 8) {
    asm volatile("setmaxnreg.inc.sync.aligned.u32 216;");
    if (warp > 0 && warp < EPF) early_pf();
    if (elect()) {
#pragma unroll 1
      for (int s = NQ + warp; s < NSTEP + 5; s += 8) { mbar_init(FULL(s), 2); mbar_init(EMPTY(s), 2); mbar_init(DATA(s), 1); }
      if (warp == 7) mbar_init(BAR(B_HDATA), 1);
      fence_async_smem();
    }
    __syncwarp();
    bar_arrive<5, 288>();
    const int wg = warp >> 2, w = warp & 3;
    const bool lead = (tid & 127) == 0;
    const bool keeper = (wg == (int)r);
    const int rho = lane >> 2, q = lane & 3;
    const uint32_t dbase = (base & 0x3FFFF) >> 4, dwg = dbase + wg * (8 * KB >> 4);
    float accG[64];
    const uint32_t dsend = dbase, dkeep = dbase + 512;
    auto g_issue = [&](int n) {
      mbar_wait(FULL(NQ + n));
      TSG(0, 64 + (wg ^ (int)r) * 64 + NQ + n);
      const uint32_t o = g_off(n) >> 4;
      wg_fence();
#pragma unroll
      for (int k = 0; k < 4; k++)
        Wgmma<128, 1, 1, H128, H128>::run(accG, dwg + o + dlo(16 * KB + k * 2048, 8192), dbase + o + dlo(k * 2048, 8192), (n | k) != 0);
      wg_commit();
    };
    auto g_step = [&](int n) {
      g_issue(n);
      wg_wait<1>();
      if (lead) mbar_arrive(EMPTY(NQ + n - 1));
    };
    uint32_t Qp[10][2], Kp[10][2], Vt[10][2];
    {
      float acc[96], acr[24];
      const uint32_t rempty = mapa(EMPTY(0), r ^ 1);
#pragma unroll 1
      for (int s = 0; s < NQ; s++) {
        mbar_wait(FULL(s));
        TSG(0, 64 + (wg ^ (int)r) * 64 + s);
        const uint32_t o = q_off(s) >> 4;
        wg_fence();
#pragma unroll
        for (int k = 0; k < 4; k++) {
          Wgmma<48, 0, 1, H128, H32>::run(acr, dwg + o + dlo(k * 32, 16), dbase + o + dlo(28 * KB + (k >> 1) * 16 * KB + (k & 1) * 512, 1024), (s | k) != 0);
          Wgmma<192, 0, 1, H128, H128>::run(acc, dwg + o + dlo(k * 32, 16), dbase + o + dlo(16 * KB + (k >> 1) * 16 * KB + (k & 1) * 2048, 4096), (s | k) != 0);
        }
        wg_commit();
        wg_wait<1>();
        if (s > 0 && lead) { mbar_arrive(EMPTY(s - 1)); mbar_arrive_remote(rempty + (s - 1) * 8); }
      }
      if (ALIGN) bar_sync<1, 256>();
      g_issue(0);
      wg_wait<1>();
      reg_fence(acc); reg_fence(acr);
      if (lead) { mbar_arrive(EMPTY(NQ - 1)); mbar_arrive_remote(rempty + (NQ - 1) * 8); }
      TSG(1, 17 + (wg ^ (int)r) * 16);
#pragma unroll
      for (int c = 0; c < 10; c++) {
        const float* ak = c < 8 ? acc + 4 * (8 + c) : acr + 4 * (c - 6);
        const float* av = c < 8 ? acc + 4 * (16 + c) : acr + 4 * (c - 4);
        Kp[c][1] = pack2(ak[2], ak[3]); Vt[c][1] = movm(pack2(av[2], av[3]));
      }
      mbar_wait(EMPTY(7));
      mbar_wait(BAR(B_LNDONE));
      const uint32_t dst = base + HALO_OFF + (w == 3 ? 8 + wg : warp + 1) * 2560;
#pragma unroll
      for (int c = 0; c < 2; c++) {
        sts128(dst + c * 1280 + lane * 16, Kp[5 * c][1], Kp[5 * c + 1][1], Kp[5 * c + 3][1], Kp[5 * c + 4][1]);
        sts128(dst + c * 1280 + 512 + lane * 16, Kp[5 * c + 2][1], Vt[5 * c][1], Vt[5 * c + 1][1], Vt[5 * c + 2][1]);
        sts64(dst + c * 1280 + 1024 + lane * 8, Vt[5 * c + 3][1], Vt[5 * c + 4][1]);
      }
      if (WFENCE) fence_async_smem();
      bar_arrive<8, 288>();
      g_step(1);
#pragma unroll
      for (int c = 0; c < 10; c++) {
        float* aq = c < 8 ? acc + 4 * c : acr + 4 * (c - 8);
        float* ak = c < 8 ? acc + 4 * (8 + c) : acr + 4 * (c - 6);
        float* av = c < 8 ? acc + 4 * (16 + c) : acr + 4 * (c - 4);
        asm volatile("" : "+f"(aq[0]), "+f"(aq[2]), "+f"(ak[0]), "+f"(av[0])::"memory");
        Qp[c][0] = pack2(aq[0], aq[1]); Qp[c][1] = pack2(aq[2], aq[3]);
        Kp[c][0] = pack2(ak[0], ak[1]); Vt[c][0] = movm(pack2(av[0], av[1]));
      }
    }
#pragma unroll 1
    for (int n = 2; n < ATT0; n++) g_step(n);
    mbar_wait(EMPTY(NQ + 2));
    mbar_wait(BAR(B_HALO));
    {
      const bool e0 = 2 * q > rho, e1 = 2 * q + 1 > rho, first = (qm == 0 && w == 0), lo = q < 2;
      uint32_t maskE = (e0 ? 0xFFFFu : 0u) | (e1 ? 0xFFFF0000u : 0u);
      uint32_t inv0 = (first && e0) ? 0xFFFFu : 0u, inv1 = (first && e1) ? 0xFFFFu : 0u;
      const uint32_t hsrc = base + HALO_OFF + warp * 2560;
      uint32_t odst = base + OST_OFF + (warp * 16 + (lane & 15)) * 160 + (lane >> 4) * 16;
      uint32_t K0[10], V0[10], Qm[4][2];
#pragma unroll
      for (int c = 0; c < 2; c++) {
        const uint4 a = lds128(hsrc + c * 1280 + lane * 16), b = lds128(hsrc + c * 1280 + 512 + lane * 16);
        K0[5 * c] = a.x; K0[5 * c + 1] = a.y; K0[5 * c + 3] = a.z; K0[5 * c + 4] = a.w;
        K0[5 * c + 2] = b.x; V0[5 * c] = b.y; V0[5 * c + 1] = b.z; V0[5 * c + 2] = b.w;
        lds64(hsrc + c * 1280 + 1024 + lane * 8, V0[5 * c + 3], V0[5 * c + 4]);
      }
#pragma unroll
      for (int h = 0; h < 4; h++) {
        Qm[h][0] = (lo != (h & 1)) ? Qp[5 * (h >> 1) + 2][0] : 0u; Qm[h][1] = (lo != (h & 1)) ? Qp[5 * (h >> 1) + 2][1] : 0u;
        asm volatile("" : "+r"(Qm[h][0]), "+r"(Qm[h][1]));
      }
      asm volatile("" : "+r"(maskE), "+r"(inv0), "+r"(inv1), "+r"(odst));
      wg_wait<0>();
      if (lead) mbar_arrive(EMPTY(NQ + ATT0 - 1));
      mbar_wait(FULL(NQ + ATT0));
      TSG(1, 30 + (wg ^ (int)r) * 16);
      float S[4][3][4], O[4][3][4], sm[4][4];
#pragma unroll
      for (int h = 0; h < 4; h++) {
        const int G = 5 * (h >> 1) + 2, H = G - 2 + 3 * (h & 1);
        mma1688z(S[h][0], Qm[h][0], Qm[h][1], K0[G]); mma1688z(S[h][1], Qm[h][0], Qm[h][1], Kp[G][0]); mma1688z(S[h][2], Qm[h][0], Qm[h][1], Kp[G][1]);
        mma16816(S[h][0], Qp[H][0], Qp[H][1], Qp[H + 1][0], Qp[H + 1][1], K0[H], K0[H + 1]);
        mma16816(S[h][1], Qp[H][0], Qp[H][1], Qp[H + 1][0], Qp[H + 1][1], Kp[H][0], Kp[H + 1][0]);
        mma16816(S[h][2], Qp[H][0], Qp[H][1], Qp[H + 1][0], Qp[H + 1][1], Kp[H][1], Kp[H + 1][1]);
      }
#pragma unroll
      for (int h = 0; h < 4; h++) {
        uint32_t P0, P1;
        win_softmax(S[h], e0, e1, inv0, inv1, P0, P1);
        const int g0 = 5 * (h >> 1) + 2 * (h & 1);
        mma1688z(sm[h], P0, P1, 0x3F803F80u);
#pragma unroll
        for (int c = 0; c < 3; c++) mma1688z(O[h][c], P0 & maskE, 0u, V0[g0 + c]);
#pragma unroll
        for (int c = 0; c < 3; c++) mma16816(O[h][c], P0 & ~maskE, P1 & maskE, 0u, P1 & ~maskE, Vt[g0 + c][0], Vt[g0 + c][1]);
      }
#pragma unroll
      for (int hp = 0; hp < 2; hp++) {
        float (&A)[3][4] = O[2 * hp];
        float (&B)[3][4] = O[2 * hp + 1];
        const float a0 = rcp(sm[2 * hp][0]), a1 = rcp(sm[2 * hp][2]), b0 = rcp(sm[2 * hp + 1][0]), b1 = rcp(sm[2 * hp + 1][2]);
        stsm4(odst + hp * 80, pack2(A[0][0] * a0, A[0][1] * a0), pack2(A[0][2] * a1, A[0][3] * a1), pack2(A[1][0] * a0, A[1][1] * a0), pack2(A[1][2] * a1, A[1][3] * a1));
        stsm4(odst + hp * 80 + 48, pack2(B[1][0] * b0, B[1][1] * b0), pack2(B[1][2] * b1, B[1][3] * b1), pack2(B[2][0] * b0, B[2][1] * b0), pack2(B[2][2] * b1, B[2][3] * b1));
        const float c0 = lo ? a0 : b0, c1 = lo ? a1 : b1;
        stsm2(odst + hp * 80 + 32, pack2((lo ? A[2][0] : B[0][0]) * c0, (lo ? A[2][1] : B[0][1]) * c0), pack2((lo ? A[2][2] : B[0][2]) * c1, (lo ? A[2][3] : B[0][3]) * c1));
      }
      if (WFENCE) fence_async_smem();
      bar_sync<2, 288>();
    }
    TSG(1, 19 + (wg ^ (int)r) * 16);
#pragma unroll 1
    for (int n = ATT0; n < NG - LEADG; n++) {
      g_issue(n);
      wg_wait<1>();
      if (lead && n != ATT0) mbar_arrive(EMPTY(NQ + n - 1));
    }
    const uint32_t rcv = base + RECV_OFF;
    float3 gt0, gt1;
    {
      float accS[32], accK[32];
#pragma unroll
      for (int n = NG - LEADG; n < NG; n++) {
        mbar_wait(FULL(NQ + n));
        TSG(0, 64 + (wg ^ (int)r) * 64 + NQ + n);
        const uint32_t o = g_off(n) >> 4;
        wg_fence();
#pragma unroll
        for (int k = 0; k < 4; k++) Wgmma<64, 1, 1, H128, H128>::run(accS, dwg + o + dlo(16 * KB + k * 2048, 8192), dsend + o + dlo(k * 2048, 8192), n != NG - LEADG || k);
        wg_commit();
        if (n == NG - LEADG) {
          wg_wait<1>(); reg_fence(accG);
          if (lead) mbar_arrive(EMPTY(NQ + n - 1));
        }
      }
      const uint32_t rdst = mapa(rcv + warp * 1024 + lane * 16, r ^ 1), rbar = mapa(BAR(B_RECVG), r ^ 1), half = 0x3F003F00u;
      uint32_t bb[8];
      ldsm4(base + B1_OFF + (lane >> 3) * 16, bb[0], bb[1], bb[2], bb[3]);
      ldsm4(base + B1_OFF + 64 + (lane >> 3) * 16, bb[4], bb[5], bb[6], bb[7]);
      const float4* gp = pt.sc->gate + pm * 128 + warp * 16 + rho;
      asm volatile("ld.relaxed.gpu.global.v2.f32 {%0,%1}, [%3];\nld.relaxed.gpu.global.f32 %2, [%3+8];" : "=f"(gt0.x), "=f"(gt0.y), "=f"(gt0.z) : "l"(gp) : "memory");
      asm volatile("ld.relaxed.gpu.global.v2.f32 {%0,%1}, [%3];\nld.relaxed.gpu.global.f32 %2, [%3+8];" : "=f"(gt1.x), "=f"(gt1.y), "=f"(gt1.z) : "l"(gp + 8) : "memory");
      TSG(2, 20 + (wg ^ (int)r) * 16);
      wg_fence();
#pragma unroll
      for (int e = 0; e < 4 * LEADG; e++) {
        const int n = NG - LEADG + (e >> 2), k = e & 3;
        Wgmma<64, 1, 1, H128, H128>::run(accK, dwg + (g_off(n) >> 4) + dlo(16 * KB + k * 2048, 8192), dkeep + (g_off(n) >> 4) + dlo(k * 2048, 8192), e);
        if (k == 0 || k == 3) wg_commit();
        if (k == 0) {
          wg_wait<1>();
          if (e == 0) reg_fence(accS); else if (lead) mbar_arrive(EMPTY(NQ + n - 1));
        }
        if (e % SDIV == 0 && e / SDIV < 4) {
          const int c = e / SDIV;
          float a[8];
#pragma unroll
          for (int f = 0; f < 8; f++) a[f] = accS[8 * c + f] + accG[8 * c + f];
          const uint32_t h0 = hmul2(bb[2 * c], half), h1 = hmul2(bb[2 * c + 1], half);
          st_async4(rdst + (c >> 1) * 8192 + (c & 1) * 512, hfma2(pack2(a[0], a[1]), half, h0), hfma2(pack2(a[2], a[3]), half, h0),
                    hfma2(pack2(a[4], a[5]), half, h1), hfma2(pack2(a[6], a[7]), half, h1), rbar + (c >> 1) * 8);
        }
      }
      wg_wait<0>();
      reg_fence(accK);
      if (lead) mbar_arrive(EMPTY(SP - 1));
      TSG(2, 21 + (wg ^ (int)r) * 16);
      uint32_t udst = rcv + (warp * 16 + (lane & 15)) * 64 + (((lane >> 4) ^ ((lane >> 1) & 3)) << 4), usrc = rcv + warp * 1024 + lane * 16;
      float a[16];
#pragma unroll
      for (int e = 0; e < 16; e++) a[e] = accK[e] + accG[32 + e];
#pragma unroll
      for (int hf = 0; hf < 2; hf++) {
        mbar_wait(BAR(B_RECVG + hf));
        if (hf == 0) TSG(2, 22 + (wg ^ (int)r) * 16);
        const uint4 v0 = lds128(usrc), v1 = lds128(usrc + 512);
        __syncwarp();
        auto ge = [&](float a0, float a1, uint32_t p) { return pack2(gelu_half(fmaf(a0, 0.5f, bf_lo(p))), gelu_half(fmaf(a1, 0.5f, bf_hi(p)))); };
        stsm4(udst, ge(a[0], a[1], v0.x), ge(a[2], a[3], v0.y), ge(a[4], a[5], v0.z), ge(a[6], a[7], v0.w));
        stsm4(udst ^ 32, ge(a[8], a[9], v1.x), ge(a[10], a[11], v1.y), ge(a[12], a[13], v1.z), ge(a[14], a[15], v1.w));
        if (WFENCE) fence_async_smem();
        asm volatile("bar.arrive %0, 288;" ::"r"(3 + hf) : "memory");
        udst += 8192; usrc += 8192;
#pragma unroll
        for (int e = 0; e < 16; e++) a[e] = accK[16 + e] + accG[48 + e];
      }
    }
    TSG(2, 23 + (wg ^ (int)r) * 16);
    float accA[80];
#pragma unroll 1
    for (int n = 0; n < NPO; n++) {
      mbar_wait(FULL(SP + n));
      TSG(0, 64 + (wg ^ (int)r) * 64 + SP + n);
      const uint32_t a = dwg + (pa_off(n) >> 4), b = dbase + (pb_off(n) >> 4);
      wg_fence();
#pragma unroll
      for (int k = 0; k < 4; k++) Wgmma<160, 0, 1, H128, H64>::run(accA, a + dlo(k * 32, 16), b + dlo(k * 1024, 4096), (n | k) != 0);
      wg_commit();
      wg_wait<1>();
      if (lead && n) mbar_arrive(EMPTY(SP + n - 1));
    }
    TSG(2, 24 + (wg ^ (int)r) * 16);
    float accY[80];
    auto py_mma = [&](int sl, bool acc) {
      const uint32_t a = dwg + (pa_off(sl) >> 4), b = dbase + (pb_off(sl) >> 4);
#pragma unroll
      for (int k = 0; k < 4; k++) Wgmma<160, 1, 0, H128, H128>::run(accY, a + dlo(k * 2048, 8192), b + dlo(k * 32, 16), acc || k != 0);
      wg_commit();
    };
    wg_wait<0>();
    reg_fence(accA);
    if (lead) mbar_arrive(EMPTY(SP + NPO - 1));
    {
      const float c0 = keeper ? gt0.z : 0.f, c1 = keeper ? gt1.z : 0.f;
#pragma unroll
      for (int e = 0; e < 80; e++) accA[e] = (e & 2) ? fmaf(gt1.x, accA[e], c1) : fmaf(gt0.x, accA[e], c0);
      reg_fence(accA);
    }
    static_assert(LEADP == 4, "staging buffer lives in the slot of k-block NP - 5");
    {
      int sl = 0;
#pragma unroll 1
      for (int n = NPO; n < NP - (keeper ? LEADP : 0); n++) {
        mbar_wait(FULL(SP + n));
        TSG(0, 64 + (wg ^ (int)r) * 64 + SP + n);
        wg_fence();
        py_mma(sl, n != NPO);
        if (n == NP - 1) bar_arrive<10, 256>();
        sl = sl == 4 ? 0 : sl + 1;
        wg_wait<1>();
        if (lead && n != NPO) mbar_arrive(EMPTY(SP + n - 1));
      }
    }
    if (keeper) {
      wg_wait<0>();
      if (lead) mbar_arrive(EMPTY(NSTEP - LEADP - 1));
      bar_sync<10, 256>();
      TSG(0, 64 + NSTEP - LEADP);
#pragma unroll 1
      for (int n = NP - LEADP; n < NP; n++) { wg_fence(); py_mma(n < 15 ? n - 10 : n - 15, true); }
    }
    mbar_wait(keeper ? EMPTY(NSTEP - LEADP - 1) : BAR(B_XFREE));
    TSG(3, 25 + (wg ^ (int)r) * 16);
    wg_wait<0>();
    reg_fence(accY);
    TSG(3, 26 + (wg ^ (int)r) * 16);
    auto mix = [&](int e) {
      const float om = (e & 1) ? gt1.y : gt0.y;
      return pack2(fmaf(om, accY[2 * e], accA[2 * e]), fmaf(om, accY[2 * e + 1], accA[2 * e + 1]));
    };
    const uint32_t xch = rcv + w * 1024 + lane * 16;
    const uint32_t rdst = mapa(xch, r ^ 1), rbar = mapa(BAR(B_RECVP), r ^ 1);
    const uint32_t odst = base + OUTST_OFF + (w * 16 + (lane & 15)) * 64 + (((lane >> 4) ^ ((lane >> 1) & 3)) << 4);
#pragma unroll
    for (int c = 0; c < 5; c++) {
      uint32_t pk[8];
      uint4 v0, v1;
      if (keeper) { mbar_wait(BAR(B_RECVP + c)); v0 = lds128(xch + c * 4096); v1 = lds128(xch + c * 4096 + 512); }
      if (c == 0) TSG(3, 27 + (wg ^ (int)r) * 16);
#pragma unroll
      for (int e = 0; e < 8; e++) pk[e] = mix(8 * c + e);
      if (keeper) {
        stsm4(odst + c * 4096, hadd2(pk[0], v0.x), hadd2(pk[1], v0.y), hadd2(pk[2], v0.z), hadd2(pk[3], v0.w));
        stsm4((odst ^ 32) + c * 4096, hadd2(pk[4], v1.x), hadd2(pk[5], v1.y), hadd2(pk[6], v1.z), hadd2(pk[7], v1.w));
        if (WFENCE) fence_async_smem();
        asm volatile("bar.arrive %0, 160;" ::"r"(11 + c) : "memory");
      } else {
        {
          st_async4(rdst + c * 4096, pk[0], pk[1], pk[2], pk[3], rbar + c * 8);
          st_async4(rdst + c * 4096 + 512, pk[4], pk[5], pk[6], pk[7], rbar + c * 8);
        }
      }
    }
    TSG(3, 28 + (wg ^ (int)r) * 16);
  } else if (warp >= 12) {
    asm volatile("setmaxnreg.dec.sync.aligned.u32 48;");
    const int lw = warp - 12;
    const int row = r * 1024 + lw * 64 + g * 8 + i;
    uint2 gw[5], xn[5];
#pragma unroll
    for (int c = 0; c < 5; c++) gw[c] = ldg64((const uint2*)pt.gw + c * 32 + lane);
    const float b2v = __bfloat162float(pt.b2[row + (lane & 3) * 256]);
    const unsigned ep0 = ld_relaxed(epp);
    wait_until(t0 + LNDELAY);
    const uint2* xp = (const uint2*)(pt.x + (size_t)row * D_) + lane;
#pragma unroll 1
    for (int k = -1; k < 4; k++) {
      uint32_t xv[10];
#pragma unroll
      for (int c = 0; c < 5; c++) { xv[2 * c] = xn[c].x; xv[2 * c + 1] = xn[c].y; }
      if (k < 3) {
#pragma unroll
        for (int c = 0; c < 5; c++) xn[c] = ldg64(xp + c * 32);
        xp += 256 * D_ / 4;
      }
      const uint32_t st = base + hst_off(k) + lw * HPITCH;
      if (k >= 0) {
        float s0 = 0.f, s1 = 0.f, q0 = 0.f, q1 = 0.f, z0 = 0.f, z1 = 0.f;
#pragma unroll
        for (int c = 0; c < 10; c++) {
          const float lo = bf_lo(xv[c]), hi = bf_hi(xv[c]);
          const uint32_t p = hmul2(xv[c], (c & 1) ? gw[c >> 1].y : gw[c >> 1].x);
          s0 += lo; s1 += hi; q0 = fmaf(lo, lo, q0); q1 = fmaf(hi, hi, q1); z0 += bf_lo(p); z1 += bf_hi(p);
        }
        float sx = s0 + s1, sq = q0 + q1, sz = z0 + z1;
#pragma unroll
        for (int o = 1; o < 32; o <<= 1) { sx += __shfl_xor_sync(0xffffffffu, sx, o); sq += __shfl_xor_sync(0xffffffffu, sq, o); sz += __shfl_xor_sync(0xffffffffu, sz, o); }
        const float mean = sx * (1.f / D_), var = fmaxf(fmaf(-mean, mean, sq * (1.f / D_)), 0.f);
        float sd;
        asm("sqrt.approx.ftz.f32 %0, %1;" : "=f"(sd) : "f"(bf_round(bf_round(var) + 1e-5f)));
        const float rs = rcp(bf_round(sd)), rh = bf_round(rs);
        const uint32_t r1 = pack2(rh, rh), r2 = pack2(rs - rh, rs - rh), mb = pack2(mean, mean);
        const float gg = bf_round(rcp(1.f + ex2(-1.4426950408889634f * bf_round(sz)))), om = bf_round(1.f - gg);
#pragma unroll
        for (int c = 0; c < 5; c++) {
          const uint32_t a = hsub2(xv[2 * c], mb), b = hsub2(xv[2 * c + 1], mb);
          sts64(st + c * 256 + lane * 8, hfma2(a, r1, hmul2(a, r2)), hfma2(b, r1, hmul2(b, r2)));
        }
        if (lane == k) sts128(base + GST_OFF + (k * 4 + lw) * 16, __float_as_uint(gg), __float_as_uint(om), __float_as_uint(om * b2v), 0);
        __syncwarp();
        if (lane == 0) mbar_arrive(BAR(B_LNROW + k));
        TSG(6, 16 + k);
      }
    }
    const unsigned ep = __shfl_sync(0xffffffffu, ep0, 0) + 1;
    mbar_wait(FULL(4));
    if (lw == 3) {
      if (elect()) {
        asm volatile("mbarrier.expect_tx.relaxed.cta.shared::cta.b64 [%0], 128;" ::"r"(BAR(B_HALO)) : "memory");
        bulk_ld(base + B1_OFF, pt.b1 + gf * 128 + (r ^ 1) * 64, 128, BAR(B_HALO));
      }
      __syncwarp();
      if (ep == 1) mbar_wait(BAR(B_HALL));
      mbar_wait(EMPTY(NQ + HG));
      if ((FL & 1) && qm) await(pt.sc->cnt + (C_HALO + qm * 8 + qj) * 32, ep);
      TSG(4, 9);
      for (uint32_t par = 0;; par ^= 1) {
        if (elect()) {
          mbar_expect_tx(BAR(B_HDATA), 5120);
          const uint4* src = pt.sc->halo + ((ep & 1) * 136 + qm * 8 + qj) * 320;
          bulk_ld(base + HALO_OFF, src, 2560, BAR(B_HDATA));
          bulk_ld(base + HALO_OFF + 4 * 2560, src + 160, 2560, BAR(B_HDATA));
        }
        __syncwarp();
        mbar_wait_par(BAR(B_HDATA), par);
        const uint32_t a = base + HALO_OFF + min(lane, 19) * 128 + 124;
        if (!__any_sync(0xffffffffu, max(lds32(a), lds32(a + 4 * 2560)) == ~0u)) break;
        __nanosleep(RGAP);
      }
      if (lane == 0) mbar_arrive(BAR(B_HALO));
      TSG(4, 14);
    }
    if (lw == 1 || lw == 2) {
      int sl = lw - 1;
      const uint32_t last = base + lane * 128 + ((lane & 7) ^ 7) * 16 + 12;
#pragma unroll 1
      for (int n = lw - 1 - NG; n < NP; n += 2) {
        const bool po = (unsigned)n < NPO;
        const uint32_t a = last + (po ? pa_off(sl) : n < 0 ? g_off(n + NG) + 16 * KB : pb_off(sl));
        const uint32_t b = po ? a ^ 0x7C : n < 0 ? a : a + 4096;
        for (uint32_t par = 0;; par ^= 1) {
          mbar_wait_par(DATA(SP + n), par);
          uint32_t m = max(max(max(lds32(a), lds32(a + 4096)), max(lds32(a + 8192), lds32(a + 12288))), lds32(b + 12288));
          if (po) m = max(max(m, lds32(b)), max(lds32(b + 4096), lds32(b + 8192)));
          if (!__any_sync(0xffffffffu, m == ~0u)) break;
          __nanosleep(RGAP);
          if (elect()) { if (n < 0) h_load(n + NG, ep & 1); else dep_load(n, sl, ep & 1); }
          __syncwarp();
        }
        if (lane == 0) mbar_arrive(FULL(SP + n));
        if (n >= 0) sl = sl >= 3 ? sl - 3 : sl + 2;
      }
    }
    if (lane == 0) {
      if (lw == 0) {
        int n = 0;
        while (!mbar_try(BAR(B_RECVP + 4))) {
          __nanosleep(100);
          if (++n > (1 << 23)) asm volatile("st.global.u32 [%0], 0;" ::"l"((char*)pt.sc + 1) : "memory");
        }
      }
    }
  } else {
    asm volatile("setmaxnreg.dec.sync.aligned.u32 32;");
    if (warp > 8) {
      unsigned* cnt = pt.sc->cnt;
      const unsigned ep = __shfl_sync(0xffffffffu, ld_relaxed(epp), 0) + 1;
      const bool one = elect();
      if (warp == 9) {
        const int row0 = r * 1024 + g * 8 + i;
#pragma unroll 1
        for (int pass = ep == 1 ? 0 : 1; pass < 2; pass++) {
          if (pass) {
            __nv_bfloat16* hp = pt.sc->h + (size_t)((ep & 1) * S_ + row0) * D_;
#pragma unroll 1
            for (int k = 0; k < 4; k++) {
              mbar_wait(BAR(B_LNROW + k));
              if (one) {
                if (k == 1) { bulk_wait0(); sts64(BAR(UTIME), 0, ep); mbar_arrive(BAR(B_HROW0)); }
                fence_async_smem();
#pragma unroll
                for (int j = 0; j < 4; j++) bulk_st(hp + (k * 4 + j) * 64 * D_, base + hst_off(k) + j * 1280, 1280);
                bulk_commit();
              }
              __syncwarp();
            }
            if (lane < 16) *(uint4*)(pt.sc->gate + row0 + lane * 64) = lds128(base + GST_OFF + lane * 16);
            __syncwarp();
            if (one) {
              bulk_wait0();
              mbar_arrive(BAR(B_LNDONE));
              TSG(4, 0);
              asm volatile("red.release.gpu.global.add.u32 [%0], 1;" ::"l"(cnt + (C_H + (i & 3)) * 32) : "memory");
              TSG(4, 8);
            }
            mbar_wait(FULL(4));
          }
          const int par = (ep ^ pass) & 1;
          const uint4 mark = make_uint4(~0u, ~0u, ~0u, ~0u);
          uint4* po = (uint4*)(pt.sc->o + (size_t)(par * S_ + qm * 128 + (lane >> 2)) * D_ + ((qj * 5 + 4) >> 2) * 64 - 16) + (lane & 3);
          uint4* pu = (uint4*)(pt.sc->u + (size_t)(par * D_ + gd * 128 + (lane >> 1)) * F_ + (gf * 2 + r) * 64 + 48) + (lane & 1);
          uint4* ph = pt.sc->halo + (par * 136 + qm * 8 + qj + 8) * 320 + (lane >> 1) * 8 + 6 + (lane & 1);
          uint4* pg = (uint4*)(pt.sc->h + (size_t)(par * S_ + row0 + (lane >> 1) * 64) * D_) + 6 + (lane & 1);
#pragma unroll 1
          for (int k = 0; k < 8; k++) {
            if (pass) { mbar_wait(EMPTY(PST + k)); __nanosleep(PGAP); }
            po[0] = mark; po[D_] = mark; po += 2 * D_;
            if (hasG) *pu = mark;
            pu += 2 * F_;
            pg[k * 8] = mark;
            if (k < 5) *(k < 3 ? ph + k * 96 : pg + (k + 5) * 8) = mark;
          }
          if (!pass) __threadfence();
          __syncwarp();
        }
        TSG(4, 3);
        *epp = ep;
      }
      else if (warp == 11) {
        mbar_wait(FULL(1));
        if (one) {
          mbar_expect_tx(BAR(B_RECVG), 8 * KB); mbar_expect_tx(BAR(B_RECVG + 1), 8 * KB);
#pragma unroll 1
          for (int k = 0; k < 9; k++) asm volatile("prefetch.tensormap [%0];" ::"l"(&mp.h + k) : "memory");
        }
        mbar_wait(BAR(B_LNDONE));
        __nanosleep(1500);
        while (!__all_sync(0xffffffffu, (int)(ld_acquire(cnt + (C_H + (lane & 3)) * 32) - ep * 32) >= 0)) {}
        asm volatile("fence.proxy.async.global;" ::: "memory");
        if (one) mbar_arrive(BAR(B_HALL));
        TSG(4, 1);
        if (one) {
          mbar_wait(BAR(B_OFREE));
          if (FL & 2) await(cnt + (C_O + pm * 2 + r) * 32, ep * 4);
          TSG(4, 4);
          int sl = 0; uint32_t tl = t0;
#pragma unroll 1
          for (int n = 0; n < NP; n++) {
            mbar_wait(EMPTY(max(n + (n < 2 ? 20 : 21), POG)));
            if (FL & 4) {
              if (n == NPO) { await(cnt + (C_U + r * 2) * 32, ep * 5 * U0); TSG(4, 6); }
              if (n == NPO + U0) mbar_wait(BAR(B_USTAGED));
            } else if (n == NPO) { mbar_wait(BAR(B_USTAGED)); wait_until(lds32(BAR(UTIME)) + USPEC); TSG(4, 6); }
            wait_until(tl + (n < NPO ? PSTAG : USTAG));
            tl = clk();
            dep_load(n, sl, ep & 1);
            sl = sl == 4 ? 0 : sl + 1;
            TSG(5, 192 + SP + n);
          }
        }
      } else {
        if (one) {
          bar_sync<8, 288>();
          fence_async_smem();
          bulk_st(pt.sc->halo + ((ep & 1) * 136 + qm * 8 + qj + 8) * 320, base + HALO_OFF + 8 * 2560, 5120);
          mbar_arrive(BAR(B_HALO));
          if (FL & 1) { bulk_commit(); bulk_wait0(); hint(cnt + (C_HALO + qm * 8 + qj + 8) * 32); }
          TSG(4, 15);
          bar_sync<2, 288>();
          fence_async_smem();
          TSG(4, 7);
          tma3d_st(&mp.ost, qj * 80, qm * 64 + (ep & 1) * 1024, 0, base + OST_OFF);
          bulk_commit(); bulk_wait0();
          if (FL & 2) hint(cnt + (C_O + qm * 2 + (qj >> 2)) * 32);
          mbar_arrive(BAR(B_OFREE));
          TSG(4, 10);
#pragma unroll 1
          for (int hf = 0; hf < 2; hf++) {
            asm volatile("bar.sync %0, 288;" ::"r"(3 + hf) : "memory");
            fence_async_smem();
            TSG(4, 11 + hf);
            if (hasG) tma2d_st(&mp.ust, (gf * 2 + r) * 64 + hf * 32, gd * 128 + (ep & 1) * D_, base + RECV_OFF + hf * 8192);
          }
          bulk_commit();
          if (!(FL & 4)) { sts64(BAR(UTIME), clk(), 0); mbar_arrive(BAR(B_USTAGED)); }
          bulk_wait0();
          if (FL & 4) {
            const int kb = gf * 2 + r, kh = kb >= 12;
            if (hasG) hint(cnt + (C_U + kh * 2 + (kb - kh * 12 >= U0)) * 32);
            TSG(4, 13);
            await(cnt + (C_U + r * 2 + 1) * 32, ep * (60 - 5 * U0));
            mbar_arrive(BAR(B_USTAGED));
            TSG(4, 5);
          }
#pragma unroll 1
          for (int c = 0; c < 5; c++) mbar_expect_tx(BAR(B_RECVP + c), 4 * KB);
          mbar_arrive_remote(mapa(BAR(B_XFREE), r ^ 1));
#pragma unroll 1
          for (int c = 0; c < 5; c++) {
            asm volatile("bar.sync %0, 160;" ::"r"(11 + c) : "memory");
            fence_async_smem();
            tma2d_st(&mp.out, pn * 160 + c * 32, pm * 128 + r * 64, base + OUTST_OFF + c * 4 * KB);
          }
          bulk_commit();
          asm volatile("cp.async.bulk.wait_group.read 0;" ::: "memory");
          TSG(3, 3);
        }
      }
    } else {
#pragma unroll 1
      for (int s = 1; s < NQ; s++) {
        const uint32_t a = base + q_off(s), b = a + 16 * KB + r * 16 * KB;
        if (s == 4) bar_sync<5, 288>();
        if (s >= 4) mbar_wait(EMPTY(s - 4));
        else wait_until(t0 + s * STAGGER);
        if (elect()) {
          mbar_expect_tx(FULL(s), 46 * KB);
          tma3d(a, &mp.x, s * 64, qm * 64, 0, FULL(s));
          tma3d_mc(b, &mp.wqm, qj * 80, s * 64 + r * 32, 0, FULL(s));
          tma3d_mc(b + 12 * KB, &mp.wqr, qj * 80 + 64, s * 64 + r * 32, 0, FULL(s));
        }
        TSG(5, 192 + s);
      }
      mbar_wait(BAR(B_HROW0));
      const unsigned ep = __shfl_sync(0xffffffffu, lds32(BAR(UTIME) + 4), 0);
      if (!elect()) return;
      uint32_t tl = t0;
#pragma unroll 1
      for (int n = 0; n < NG; n++) {
        if (n == (ep == 1 ? 0 : NG - 2)) mbar_wait(BAR(B_HALL));
        mbar_wait(EMPTY(n + 4 + ((0x55550156u >> (2 * n)) & 3)));
        wait_until(tl + GSTAG);
        tl = clk();
        const uint32_t a = base + g_off(n);
        h_load(n, ep & 1);
        mbar_expect_tx(FULL(NQ + n), 16 * KB);
        tma2d(a, &mp.w1, gf * 128 + (r ^ 1) * 64, r * 1024 + n * 64, FULL(NQ + n));
        tma2d(a + 8 * KB, &mp.w1, gf * 128 + r * 64, r * 1024 + n * 64, FULL(NQ + n));
        TSG(5, 192 + NQ + n);
      }
      mbar_wait(BAR(B_OFREE));
      int sl = 0;
#pragma unroll 1
      for (int n = 0; n < NP; n++) {
        mbar_wait(EMPTY(max(n + (n < 2 ? 20 : 21), WOG)));
        wait_until(tl + PSTAG);
        tl = clk();
        const bool po = n < NPO;
        mbar_expect_tx(FULL(SP + n), po ? 20 * KB : 16 * KB);
        tma3d(base + (po ? pb_off(sl) : pa_off(sl)), po ? &mp.wo : &mp.w2, 0, (po ? r * 320 : r * 768 - NPO * 64) + n * 64, po ? pn * 5 : pm * 2, FULL(SP + n));
        sl = sl == 4 ? 0 : sl + 1;
      }
    }
  }
}

typedef CUresult (*EncFn)(CUtensorMap*, CUtensorMapDataType, cuuint32_t, void*, const cuuint64_t*, const cuuint64_t*, const cuuint32_t*,
                          const cuuint32_t*, CUtensorMapInterleave, CUtensorMapSwizzle, CUtensorMapL2promotion, CUtensorMapFloatOOBfill);

void mkmap(EncFn enc, CUtensorMap* m, const void* ptr, int rank, cuuint64_t d0, cuuint64_t d1, cuuint64_t d2, cuuint64_t s1, cuuint64_t s2,
           cuuint32_t b0, cuuint32_t b1, cuuint32_t b2, CUtensorMapSwizzle sw) {
  cuuint64_t dims[3] = {d0, d1, d2}, st[2] = {s1, s2};
  cuuint32_t box[3] = {b0, b1, b2}, es[3] = {1, 1, 1};
  enc(m, CU_TENSOR_MAP_DATA_TYPE_BFLOAT16, rank, (void*)ptr, dims, st, box, es, CU_TENSOR_MAP_INTERLEAVE_NONE, sw,
      CU_TENSOR_MAP_L2_PROMOTION_L2_128B, CU_TENSOR_MAP_FLOAT_OOB_FILL_NONE);
}

}

extern "C" void kernel_launch(void* const* d_in, const int* in_sizes, int n_in, void* d_out, int out_size) {
  (void)in_sizes; (void)n_in; (void)out_size;
  const __nv_bfloat16* x = (const __nv_bfloat16*)d_in[0];
  const __nv_bfloat16* wqkv = (const __nv_bfloat16*)d_in[1];
  const __nv_bfloat16* wo = (const __nv_bfloat16*)d_in[2];
  const __nv_bfloat16* w1 = (const __nv_bfloat16*)d_in[4];
  const __nv_bfloat16* w2 = (const __nv_bfloat16*)d_in[6];
  void* fn = nullptr; cudaDriverEntryPointQueryResult qr;
  cudaGetDriverEntryPoint("cuTensorMapEncodeTiled", &fn, cudaEnableDefault, &qr);
  EncFn enc = (EncFn)fn;
  void* psc;
  cudaGetSymbolAddress(&psc, g_sc);
  Scratch* sc = (Scratch*)psc;
  void *ph = sc->h, *po = sc->o, *pu = sc->u;
  const CUtensorMapSwizzle S128 = CU_TENSOR_MAP_SWIZZLE_128B, S64 = CU_TENSOR_MAP_SWIZZLE_64B, S0 = CU_TENSOR_MAP_SWIZZLE_NONE;
  Maps mp;
  mkmap(enc, &mp.x, x, 3, 640, 1024, 2, 2560, 1280, 64, 64, 2, S128);
  mkmap(enc, &mp.wqm, wqkv, 3, 640, 640, 3, 3840, 1280, 64, 32, 3, S128);
  mkmap(enc, &mp.wqr, wqkv, 3, 640, 640, 3, 3840, 1280, 16, 32, 3, CU_TENSOR_MAP_SWIZZLE_32B);
  mkmap(enc, &mp.h, ph, 3, 64, 4096, 10, 1280, 128, 64, 64, 2, S128);
  mkmap(enc, &mp.w1, w1, 2, 1536, 2048, 1, 3072, 0, 64, 64, 1, S128);
  mkmap(enc, &mp.old_, po, 2, 640, 4096, 1, 1280, 0, 64, 128, 1, S128);
  mkmap(enc, &mp.wo, wo, 3, 32, 640, 20, 1280, 64, 32, 64, 5, S64);
  mkmap(enc, &mp.w2, w2, 3, 64, 1536, 32, 4096, 128, 64, 64, 2, S128);
  mkmap(enc, &mp.uld, pu, 2, 1536, 1280, 1, 3072, 0, 64, 160, 1, S128);
  mkmap(enc, &mp.ost, po, 3, 640, 2048, 2, 2560, 1280, 80, 64, 2, S0);
  mkmap(enc, &mp.ust, pu, 2, 1536, 1280, 1, 3072, 0, 32, 128, 1, S64);
  mkmap(enc, &mp.out, d_out, 2, 640, 2048, 1, 1280, 0, 32, 64, 1, S64);
  Ptrs pt;
  pt.w2 = w2; pt.wo = wo; pt.sc = sc; pt.x = x; pt.wq = wqkv; pt.b1 = (const __nv_bfloat16*)d_in[5]; pt.b2 = (const __nv_bfloat16*)d_in[7]; pt.gw = (const __nv_bfloat16*)d_in[8];
  int dev = 0, sms = 0;
  cudaGetDevice(&dev);
  cudaDeviceGetAttribute(&sms, cudaDevAttrMultiProcessorCount, dev);
  if (sms == 132) {
    cudaFuncSetAttribute(fused_kernel<true>, cudaFuncAttributeMaxDynamicSharedMemorySize, SMEM_BYTES);
    fused_kernel<true><<<132, 512, SMEM_BYTES, cudaStreamPerThread>>>(pt, mp);
  } else {
    cudaFuncSetAttribute(fused_kernel<false>, cudaFuncAttributeMaxDynamicSharedMemorySize, SMEM_BYTES);
    fused_kernel<false><<<128, 512, SMEM_BYTES, cudaStreamPerThread>>>(pt, mp);
  }
}
```

```cpp
#include <cuda_runtime.h>
#include <cuda_bf16.h>
#include <cuda.h>
#include <stdint.h>
#include <stddef.h>

namespace {

constexpr int S_ = 2048, D_ = 640, F_ = 1536;
constexpr int NQ = 10, NG = 16, NPO = 5, NPY = 12, SP = NQ + NG, NP = NPO + NPY, NSTEP = SP + NP;
constexpr int KB = 1024;
constexpr int RECV_OFF = 180 * KB;
constexpr int HALO_OFF = 200 * KB;
constexpr int OST_OFF = HALO_OFF;
constexpr int HST_OFF0 = 144 * KB, HST_OFF1 = 208 * KB, HPITCH = 1280;
__host__ __device__ constexpr uint32_t hst_off(int k) { return k == 0 ? HST_OFF0 : HST_OFF1 + (k - 1) * 4 * HPITCH; }
constexpr int BAR_OFF = 225 * KB;
constexpr int B1_OFF = BAR_OFF + 1216;
constexpr int GST_OFF = B1_OFF + 128;
constexpr int SMEM_BYTES = 227 * KB;
constexpr int B_EMPTY = 48, B_HALL = 96, B_HROW0 = 97, B_LNDONE = 98, B_XFREE0 = 99, B_HALO = 100, B_OFREE = 102, B_UREADY = 103,
              B_RECVG = 104  , B_RECVP = 147  , B_HDATA = 112, EPOCH = 113  , B_XFREE = 106, B_LNROW = 107  , B_DATA = 114 - NQ  ;
#define LEADG 2
#define GSTAG 350
#define PSTAG 400
#define PST 30
#define U0 2
#define PGAP 150
#define LNDELAY 1200
#define HG 3
#define RGAP 200
#define USTAG 450
#define SDIV 2
constexpr int LEADP = 4;
#define STAGGER 750
#define ATT0 8

struct Maps { CUtensorMap x, wqm, wqr, h, w1, old_, wo, w2, uld, ost, ust, out; };
struct Scratch {
  __nv_bfloat16 h[2 * S_ * D_], o[2 * S_ * D_], u[2 * D_ * F_];
  uint4 halo[2 * 136 * 320];
  float4 gate[S_];
  unsigned cnt[(4 + 4 + 32 + 128) * 32];
};
constexpr int C_H = 0, C_U = 4, C_O = 8, C_EP = 40;
struct Ptrs { Scratch* sc; const __nv_bfloat16 *x, *wq, *gw, *b1, *b2; };
__device__ __align__(1024) Scratch g_sc;
#define TSG(grp, i)

__device__ __forceinline__ uint32_t clk() { uint32_t c; asm volatile("mov.u32 %0, %%clock;" : "=r"(c)); return c; }
__device__ __forceinline__ void wait_until(uint32_t t) { while ((int)(clk() - t) < 0) {} }
template <int N, int TA, int TB, uint32_t HA, uint32_t HB> struct Wgmma;
template <int TA, int TB, uint32_t HA, uint32_t HB> struct Wgmma<48, TA, TB, HA, HB> {
  static __device__ __forceinline__ void run(float (&d)[24], uint32_t la, uint32_t lb, int sd) {
    asm volatile("{\n.reg .pred p;\n.reg .b64 da, db;\nsetp.ne.b32 p, %26, 0;\nmov.b64 da, {%24, %29};\nmov.b64 db, {%25, %30};\n"
      "wgmma.mma_async.sync.aligned.m64n48k16.f32.bf16.bf16 {%0, %1, %2, %3, %4, %5, %6, %7, %8, %9, %10, %11, %12, %13, %14, %15, %16, %17, %18, %19, %20, %21, %22, %23}, da, db, p, 1, 1, %27, %28;\n}\n"
      : "+f"(d[0]), "+f"(d[1]), "+f"(d[2]), "+f"(d[3]), "+f"(d[4]), "+f"(d[5]), "+f"(d[6]), "+f"(d[7]), "+f"(d[8]), "+f"(d[9]), "+f"(d[10]), "+f"(d[11]), "+f"(d[12]), "+f"(d[13]), "+f"(d[14]), "+f"(d[15]), "+f"(d[16]), "+f"(d[17]), "+f"(d[18]), "+f"(d[19]), "+f"(d[20]), "+f"(d[21]), "+f"(d[22]), "+f"(d[23])
      : "r"(la), "r"(lb), "r"(sd), "n"(TA), "n"(TB), "n"(HA), "n"(HB));
  }
};
template <int TA, int TB, uint32_t HA, uint32_t HB> struct Wgmma<64, TA, TB, HA, HB> {
  static __device__ __forceinline__ void run(float (&d)[32], uint32_t la, uint32_t lb, int sd) {
    asm volatile("{\n.reg .pred p;\n.reg .b64 da, db;\nsetp.ne.b32 p, %34, 0;\nmov.b64 da, {%32, %37};\nmov.b64 db, {%33, %38};\n"
      "wgmma.mma_async.sync.aligned.m64n64k16.f32.bf16.bf16 {%0, %1, %2, %3, %4, %5, %6, %7, %8, %9, %10, %11, %12, %13, %14, %15, %16, %17, %18, %19, %20, %21, %22, %23, %24, %25, %26, %27, %28, %29, %30, %31}, da, db, p, 1, 1, %35, %36;\n}\n"
      : "+f"(d[0]), "+f"(d[1]), "+f"(d[2]), "+f"(d[3]), "+f"(d[4]), "+f"(d[5]), "+f"(d[6]), "+f"(d[7]), "+f"(d[8]), "+f"(d[9]), "+f"(d[10]), "+f"(d[11]), "+f"(d[12]), "+f"(d[13]), "+f"(d[14]), "+f"(d[15]), "+f"(d[16]), "+f"(d[17]), "+f"(d[18]), "+f"(d[19]), "+f"(d[20]), "+f"(d[21]), "+f"(d[22]), "+f"(d[23]), "+f"(d[24]), "+f"(d[25]), "+f"(d[26]), "+f"(d[27]), "+f"(d[28]), "+f"(d[29]), "+f"(d[30]), "+f"(d[31])
      : "r"(la), "r"(lb), "r"(sd), "n"(TA), "n"(TB), "n"(HA), "n"(HB));
  }
};
template <int TA, int TB, uint32_t HA, uint32_t HB> struct Wgmma<128, TA, TB, HA, HB> {
  static __device__ __forceinline__ void run(float (&d)[64], uint32_t la, uint32_t lb, int sd) {
    asm volatile("{\n.reg .pred p;\n.reg .b64 da, db;\nsetp.ne.b32 p, %66, 0;\nmov.b64 da, {%64, %69};\nmov.b64 db, {%65, %70};\n"
      "wgmma.mma_async.sync.aligned.m64n128k16.f32.bf16.bf16 {%0, %1, %2, %3, %4, %5, %6, %7, %8, %9, %10, %11, %12, %13, %14, %15, %16, %17, %18, %19, %20, %21, %22, %23, %24, %25, %26, %27, %28, %29, %30, %31, %32, %33, %34, %35, %36, %37, %38, %39, %40, %41, %42, %43, %44, %45, %46, %47, %48, %49, %50, %51, %52, %53, %54, %55, %56, %57, %58, %59, %60, %61, %62, %63}, da, db, p, 1, 1, %67, %68;\n}\n"
      : "+f"(d[0]), "+f"(d[1]), "+f"(d[2]), "+f"(d[3]), "+f"(d[4]), "+f"(d[5]), "+f"(d[6]), "+f"(d[7]), "+f"(d[8]), "+f"(d[9]), "+f"(d[10]), "+f"(d[11]), "+f"(d[12]), "+f"(d[13]), "+f"(d[14]), "+f"(d[15]), "+f"(d[16]), "+f"(d[17]), "+f"(d[18]), "+f"(d[19]), "+f"(d[20]), "+f"(d[21]), "+f"(d[22]), "+f"(d[23]), "+f"(d[24]), "+f"(d[25]), "+f"(d[26]), "+f"(d[27]), "+f"(d[28]), "+f"(d[29]), "+f"(d[30]), "+f"(d[31]), "+f"(d[32]), "+f"(d[33]), "+f"(d[34]), "+f"(d[35]), "+f"(d[36]), "+f"(d[37]), "+f"(d[38]), "+f"(d[39]), "+f"(d[40]), "+f"(d[41]), "+f"(d[42]), "+f"(d[43]), "+f"(d[44]), "+f"(d[45]), "+f"(d[46]), "+f"(d[47]), "+f"(d[48]), "+f"(d[49]), "+f"(d[50]), "+f"(d[51]), "+f"(d[52]), "+f"(d[53]), "+f"(d[54]), "+f"(d[55]), "+f"(d[56]), "+f"(d[57]), "+f"(d[58]), "+f"(d[59]), "+f"(d[60]), "+f"(d[61]), "+f"(d[62]), "+f"(d[63])
      : "r"(la), "r"(lb), "r"(sd), "n"(TA), "n"(TB), "n"(HA), "n"(HB));
  }
};
template <int TA, int TB, uint32_t HA, uint32_t HB> struct Wgmma<160, TA, TB, HA, HB> {
  static __device__ __forceinline__ void run(float (&d)[80], uint32_t la, uint32_t lb, int sd) {
    asm volatile("{\n.reg .pred p;\n.reg .b64 da, db;\nsetp.ne.b32 p, %82, 0;\nmov.b64 da, {%80, %85};\nmov.b64 db, {%81, %86};\n"
      "wgmma.mma_async.sync.aligned.m64n160k16.f32.bf16.bf16 {%0, %1, %2, %3, %4, %5, %6, %7, %8, %9, %10, %11, %12, %13, %14, %15, %16, %17, %18, %19, %20, %21, %22, %23, %24, %25, %26, %27, %28, %29, %30, %31, %32, %33, %34, %35, %36, %37, %38, %39, %40, %41, %42, %43, %44, %45, %46, %47, %48, %49, %50, %51, %52, %53, %54, %55, %56, %57, %58, %59, %60, %61, %62, %63, %64, %65, %66, %67, %68, %69, %70, %71, %72, %73, %74, %75, %76, %77, %78, %79}, da, db, p, 1, 1, %83, %84;\n}\n"
      : "+f"(d[0]), "+f"(d[1]), "+f"(d[2]), "+f"(d[3]), "+f"(d[4]), "+f"(d[5]), "+f"(d[6]), "+f"(d[7]), "+f"(d[8]), "+f"(d[9]), "+f"(d[10]), "+f"(d[11]), "+f"(d[12]), "+f"(d[13]), "+f"(d[14]), "+f"(d[15]), "+f"(d[16]), "+f"(d[17]), "+f"(d[18]), "+f"(d[19]), "+f"(d[20]), "+f"(d[21]), "+f"(d[22]), "+f"(d[23]), "+f"(d[24]), "+f"(d[25]), "+f"(d[26]), "+f"(d[27]), "+f"(d[28]), "+f"(d[29]), "+f"(d[30]), "+f"(d[31]), "+f"(d[32]), "+f"(d[33]), "+f"(d[34]), "+f"(d[35]), "+f"(d[36]), "+f"(d[37]), "+f"(d[38]), "+f"(d[39]), "+f"(d[40]), "+f"(d[41]), "+f"(d[42]), "+f"(d[43]), "+f"(d[44]), "+f"(d[45]), "+f"(d[46]), "+f"(d[47]), "+f"(d[48]), "+f"(d[49]), "+f"(d[50]), "+f"(d[51]), "+f"(d[52]), "+f"(d[53]), "+f"(d[54]), "+f"(d[55]), "+f"(d[56]), "+f"(d[57]), "+f"(d[58]), "+f"(d[59]), "+f"(d[60]), "+f"(d[61]), "+f"(d[62]), "+f"(d[63]), "+f"(d[64]), "+f"(d[65]), "+f"(d[66]), "+f"(d[67]), "+f"(d[68]), "+f"(d[69]), "+f"(d[70]), "+f"(d[71]), "+f"(d[72]), "+f"(d[73]), "+f"(d[74]), "+f"(d[75]), "+f"(d[76]), "+f"(d[77]), "+f"(d[78]), "+f"(d[79])
      : "r"(la), "r"(lb), "r"(sd), "n"(TA), "n"(TB), "n"(HA), "n"(HB));
  }
};
template <int TA, int TB, uint32_t HA, uint32_t HB> struct Wgmma<192, TA, TB, HA, HB> {
  static __device__ __forceinline__ void run(float (&d)[96], uint32_t la, uint32_t lb, int sd) {
    asm volatile("{\n.reg .pred p;\n.reg .b64 da, db;\nsetp.ne.b32 p, %98, 0;\nmov.b64 da, {%96, %101};\nmov.b64 db, {%97, %102};\n"
      "wgmma.mma_async.sync.aligned.m64n192k16.f32.bf16.bf16 {%0, %1, %2, %3, %4, %5, %6, %7, %8, %9, %10, %11, %12, %13, %14, %15, %16, %17, %18, %19, %20, %21, %22, %23, %24, %25, %26, %27, %28, %29, %30, %31, %32, %33, %34, %35, %36, %37, %38, %39, %40, %41, %42, %43, %44, %45, %46, %47, %48, %49, %50, %51, %52, %53, %54, %55, %56, %57, %58, %59, %60, %61, %62, %63, %64, %65, %66, %67, %68, %69, %70, %71, %72, %73, %74, %75, %76, %77, %78, %79, %80, %81, %82, %83, %84, %85, %86, %87, %88, %89, %90, %91, %92, %93, %94, %95}, da, db, p, 1, 1, %99, %100;\n}\n"
      : "+f"(d[0]), "+f"(d[1]), "+f"(d[2]), "+f"(d[3]), "+f"(d[4]), "+f"(d[5]), "+f"(d[6]), "+f"(d[7]), "+f"(d[8]), "+f"(d[9]), "+f"(d[10]), "+f"(d[11]), "+f"(d[12]), "+f"(d[13]), "+f"(d[14]), "+f"(d[15]), "+f"(d[16]), "+f"(d[17]), "+f"(d[18]), "+f"(d[19]), "+f"(d[20]), "+f"(d[21]), "+f"(d[22]), "+f"(d[23]), "+f"(d[24]), "+f"(d[25]), "+f"(d[26]), "+f"(d[27]), "+f"(d[28]), "+f"(d[29]), "+f"(d[30]), "+f"(d[31]), "+f"(d[32]), "+f"(d[33]), "+f"(d[34]), "+f"(d[35]), "+f"(d[36]), "+f"(d[37]), "+f"(d[38]), "+f"(d[39]), "+f"(d[40]), "+f"(d[41]), "+f"(d[42]), "+f"(d[43]), "+f"(d[44]), "+f"(d[45]), "+f"(d[46]), "+f"(d[47]), "+f"(d[48]), "+f"(d[49]), "+f"(d[50]), "+f"(d[51]), "+f"(d[52]), "+f"(d[53]), "+f"(d[54]), "+f"(d[55]), "+f"(d[56]), "+f"(d[57]), "+f"(d[58]), "+f"(d[59]), "+f"(d[60]), "+f"(d[61]), "+f"(d[62]), "+f"(d[63]), "+f"(d[64]), "+f"(d[65]), "+f"(d[66]), "+f"(d[67]), "+f"(d[68]), "+f"(d[69]), "+f"(d[70]), "+f"(d[71]), "+f"(d[72]), "+f"(d[73]), "+f"(d[74]), "+f"(d[75]), "+f"(d[76]), "+f"(d[77]), "+f"(d[78]), "+f"(d[79]), "+f"(d[80]), "+f"(d[81]), "+f"(d[82]), "+f"(d[83]), "+f"(d[84]), "+f"(d[85]), "+f"(d[86]), "+f"(d[87]), "+f"(d[88]), "+f"(d[89]), "+f"(d[90]), "+f"(d[91]), "+f"(d[92]), "+f"(d[93]), "+f"(d[94]), "+f"(d[95])
      : "r"(la), "r"(lb), "r"(sd), "n"(TA), "n"(TB), "n"(HA), "n"(HB));
  }
};

__device__ __forceinline__ uint32_t smem_u32(const void* p) { return (uint32_t)__cvta_generic_to_shared(p); }
__device__ __forceinline__ void mbar_init(uint32_t bar, int cnt) { asm volatile("mbarrier.init.shared::cta.b64 [%0], %1;" ::"r"(bar), "r"(cnt) : "memory"); }
__device__ __forceinline__ void mbar_expect_tx(uint32_t bar, uint32_t bytes) { asm volatile("mbarrier.arrive.expect_tx.shared::cta.b64 _, [%0], %1;" ::"r"(bar), "r"(bytes) : "memory"); }
__device__ __forceinline__ void mbar_arrive(uint32_t bar) { asm volatile("mbarrier.arrive.shared::cta.b64 _, [%0];" ::"r"(bar) : "memory"); }
__device__ __forceinline__ uint32_t mapa(uint32_t a, uint32_t cta) { uint32_t r; asm("mapa.shared::cluster.u32 %0, %1, %2;" : "=r"(r) : "r"(a), "r"(cta)); return r; }
__device__ __forceinline__ void mbar_arrive_remote(uint32_t rbar) { asm volatile("mbarrier.arrive.shared::cluster.b64 _, [%0];" ::"r"(rbar) : "memory"); }
__device__ __forceinline__ void mbar_wait(uint32_t bar) {
  asm volatile("{\n.reg .pred p;\nW_LOOP:\nmbarrier.try_wait.parity.shared::cta.b64 p, [%0], 0;\n@!p bra.uni W_LOOP;\n}" ::"r"(bar) : "memory");
}
__device__ __forceinline__ void mbar_wait_par(uint32_t bar, uint32_t par) {
  asm volatile("{\n.reg .pred p;\nC_LOOP:\nmbarrier.try_wait.parity.shared::cta.b64 p, [%0], %1;\n@!p bra.uni C_LOOP;\n}" ::"r"(bar), "r"(par) : "memory");
}
__device__ __forceinline__ uint32_t lds32(uint32_t a) { uint32_t v; asm volatile("ld.shared.u32 %0, [%1];" : "=r"(v) : "r"(a) : "memory"); return v; }
__device__ __forceinline__ bool mbar_try(uint32_t bar) {
  uint32_t ok;
  asm volatile("{\n.reg .pred p;\nmbarrier.test_wait.parity.shared::cta.b64 p, [%1], 0;\nselp.b32 %0, 1, 0, p;\n}" : "=r"(ok) : "r"(bar) : "memory");
  return ok;
}
__device__ __forceinline__ bool elect() {
  uint32_t ok;
  asm volatile("{\n.reg .pred p;\nelect.sync _|p, 0xffffffff;\nselp.b32 %0, 1, 0, p;\n}" : "=r"(ok));
  return ok;
}
__device__ __forceinline__ void tma2d(uint32_t dst, const CUtensorMap* m, int c0, int c1, uint32_t bar) {
  asm volatile("cp.async.bulk.tensor.2d.shared::cluster.global.mbarrier::complete_tx::bytes [%0], [%1, {%3,%4}], [%2];" ::"r"(dst), "l"(m), "r"(bar), "r"(c0), "r"(c1) : "memory");
}
__device__ __forceinline__ void tma3d(uint32_t dst, const CUtensorMap* m, int c0, int c1, int c2, uint32_t bar) {
  asm volatile("cp.async.bulk.tensor.3d.shared::cluster.global.mbarrier::complete_tx::bytes [%0], [%1, {%3,%4,%5}], [%2];" ::"r"(dst), "l"(m), "r"(bar), "r"(c0), "r"(c1), "r"(c2) : "memory");
}
__device__ __forceinline__ void tma3d_mc(uint32_t dst, const CUtensorMap* m, int c0, int c1, int c2, uint32_t bar) {
  asm volatile("cp.async.bulk.tensor.3d.shared::cluster.global.mbarrier::complete_tx::bytes.multicast::cluster [%0], [%1, {%3,%4,%5}], [%2], %6;" ::"r"(dst), "l"(m), "r"(bar), "r"(c0), "r"(c1), "r"(c2), "h"((uint16_t)3) : "memory");
}
__device__ __forceinline__ void tma2d_st(const CUtensorMap* m, int c0, int c1, uint32_t src) {
  asm volatile("cp.async.bulk.tensor.2d.global.shared::cta.bulk_group [%0, {%2,%3}], [%1];" ::"l"(m), "r"(src), "r"(c0), "r"(c1) : "memory");
}
__device__ __forceinline__ void tma3d_st(const CUtensorMap* m, int c0, int c1, int c2, uint32_t src) {
  asm volatile("cp.async.bulk.tensor.3d.global.shared::cta.bulk_group [%0, {%2,%3,%4}], [%1];" ::"l"(m), "r"(src), "r"(c0), "r"(c1), "r"(c2) : "memory");
}
__device__ __forceinline__ void bulk_commit() { asm volatile("cp.async.bulk.commit_group;" ::: "memory"); }
__device__ __forceinline__ void bulk_wait0() { asm volatile("cp.async.bulk.wait_group 0;" ::: "memory"); }
__device__ __forceinline__ void fence_async_smem() { asm volatile("fence.proxy.async.shared::cta;" ::: "memory"); }
__device__ __forceinline__ void wg_fence() { asm volatile("wgmma.fence.sync.aligned;" ::: "memory"); }
__device__ __forceinline__ void wg_commit() { asm volatile("wgmma.commit_group.sync.aligned;" ::: "memory"); }
template <int N> __device__ __forceinline__ void wg_wait() { asm volatile("wgmma.wait_group.sync.aligned %0;" ::"n"(N) : "memory"); }
template <int N> __device__ __forceinline__ void reg_fence(float (&a)[N]) {
#pragma unroll
  for (int i = 0; i < N; i++) asm volatile("" : "+f"(a[i])::"memory");
}
template <int ID, int N> __device__ __forceinline__ void bar_sync() { asm volatile("bar.sync %0, %1;" ::"n"(ID), "n"(N) : "memory"); }
template <int ID, int N> __device__ __forceinline__ void bar_arrive() { asm volatile("bar.arrive %0, %1;" ::"n"(ID), "n"(N) : "memory"); }
__host__ __device__ constexpr uint32_t dlo(uint32_t off, uint32_t lbo) { return (off >> 4) | ((lbo >> 4) << 16); }
__host__ __device__ constexpr uint32_t dhi(uint32_t sbo, uint32_t swz) { return (sbo >> 4) | (swz << 30); }
constexpr uint32_t H128 = dhi(1024, 1), H64 = dhi(512, 2), H32 = dhi(256, 3);
__device__ __forceinline__ uint32_t pack2(float lo, float hi) { uint32_t r; asm("cvt.rn.bf16x2.f32 %0, %1, %2;" : "=r"(r) : "f"(hi), "f"(lo)); return r; }
__device__ __forceinline__ float bf_lo(uint32_t v) { return __uint_as_float(v << 16); }
__device__ __forceinline__ float bf_hi(uint32_t v) { return __uint_as_float(v & 0xFFFF0000u); }
__device__ __forceinline__ float bf_round(float v) { return __bfloat162float(__float2bfloat16_rn(v)); }
__device__ __forceinline__ uint32_t movm(uint32_t a) { uint32_t d; asm volatile("movmatrix.sync.aligned.m8n8.trans.b16 %0, %1;" : "=r"(d) : "r"(a)); return d; }
__device__ __forceinline__ void stsm4(uint32_t addr, uint32_t a, uint32_t b, uint32_t c, uint32_t d) {
  asm volatile("stmatrix.sync.aligned.m8n8.x4.shared.b16 [%0], {%1,%2,%3,%4};" ::"r"(addr), "r"(a), "r"(b), "r"(c), "r"(d) : "memory");
}
__device__ __forceinline__ void stsm2(uint32_t addr, uint32_t a, uint32_t b) {
  asm volatile("stmatrix.sync.aligned.m8n8.x2.shared.b16 [%0], {%1,%2};" ::"r"(addr), "r"(a), "r"(b) : "memory");
}
__device__ __forceinline__ void sts128(uint32_t addr, uint32_t a, uint32_t b, uint32_t c, uint32_t d) {
  asm volatile("st.shared.v4.b32 [%0], {%1,%2,%3,%4};" ::"r"(addr), "r"(a), "r"(b), "r"(c), "r"(d) : "memory");
}
__device__ __forceinline__ void sts64(uint32_t addr, uint32_t a, uint32_t b) { asm volatile("st.shared.v2.b32 [%0], {%1,%2};" ::"r"(addr), "r"(a), "r"(b) : "memory"); }
__device__ __forceinline__ uint4 lds128(uint32_t addr) { uint4 v; asm volatile("ld.shared.v4.b32 {%0,%1,%2,%3}, [%4];" : "=r"(v.x), "=r"(v.y), "=r"(v.z), "=r"(v.w) : "r"(addr) : "memory"); return v; }
__device__ __forceinline__ uint32_t hmul2(uint32_t a, uint32_t b) { uint32_t d; asm("mul.rn.bf16x2 %0, %1, %2;" : "=r"(d) : "r"(a), "r"(b)); return d; }
__device__ __forceinline__ uint32_t hsub2(uint32_t a, uint32_t b) { uint32_t d; asm("sub.rn.bf16x2 %0, %1, %2;" : "=r"(d) : "r"(a), "r"(b)); return d; }
__device__ __forceinline__ void mma16816(float (&c)[4], uint32_t a0, uint32_t a1, uint32_t a2, uint32_t a3, uint32_t b0, uint32_t b1) {
  asm volatile("mma.sync.aligned.m16n8k16.row.col.f32.bf16.bf16.f32 {%0,%1,%2,%3}, {%4,%5,%6,%7}, {%8,%9}, {%0,%1,%2,%3};"
               : "+f"(c[0]), "+f"(c[1]), "+f"(c[2]), "+f"(c[3]) : "r"(a0), "r"(a1), "r"(a2), "r"(a3), "r"(b0), "r"(b1));
}
__device__ __forceinline__ void mma1688z(float (&c)[4], uint32_t a0, uint32_t a1, uint32_t b0) {
  asm volatile("mma.sync.aligned.m16n8k8.row.col.f32.bf16.bf16.f32 {%0,%1,%2,%3}, {%4,%5}, {%6}, {%7,%7,%7,%7};"
               : "=f"(c[0]), "=f"(c[1]), "=f"(c[2]), "=f"(c[3]) : "r"(a0), "r"(a1), "r"(b0), "f"(0.f));
}
__device__ __forceinline__ unsigned ld_relaxed(const unsigned* p) { unsigned v; asm volatile("ld.relaxed.gpu.global.u32 %0, [%1];" : "=r"(v) : "l"(p) : "memory"); return v; }
__device__ __forceinline__ unsigned ld_acquire(const unsigned* p) { unsigned v; asm volatile("ld.acquire.gpu.global.u32 %0, [%1];" : "=r"(v) : "l"(p) : "memory"); return v; }
__device__ __forceinline__ void hint(unsigned* p) { asm volatile("red.relaxed.gpu.global.add.u32 [%0], 1;" ::"l"(p) : "memory"); }
__device__ __forceinline__ void await(const unsigned* p, unsigned target) { while ((int)(ld_relaxed(p) - target) < 0) {} }
__device__ __forceinline__ void bulk_st(void* g, uint32_t src, uint32_t bytes) {
  asm volatile("cp.async.bulk.global.shared::cta.bulk_group [%0], [%1], %2;" ::"l"(g), "r"(src), "r"(bytes) : "memory");
}
__device__ __forceinline__ void bulk_ld(uint32_t dst, const void* g, uint32_t bytes, uint32_t bar) {
  asm volatile("cp.async.bulk.shared::cluster.global.mbarrier::complete_tx::bytes [%0], [%1], %2, [%3];" ::"r"(dst), "l"(g), "r"(bytes), "r"(bar) : "memory");
}
__device__ __forceinline__ uint2 ldg64(const uint2* p) { uint2 v; asm volatile("ld.global.nc.v2.u32 {%0,%1}, [%2];" : "=r"(v.x), "=r"(v.y) : "l"(p)); return v; }
__device__ __forceinline__ void st_async4(uint32_t raddr, uint32_t a, uint32_t b, uint32_t c, uint32_t d, uint32_t rbar) {
  asm volatile("st.async.weak.shared::cluster.mbarrier::complete_tx::bytes.v4.b32 [%0], {%1,%2,%3,%4}, [%5];" ::"r"(raddr), "r"(a), "r"(b), "r"(c), "r"(d), "r"(rbar) : "memory");
}
__device__ __forceinline__ void lds64(uint32_t addr, uint32_t& a, uint32_t& b) { asm volatile("ld.shared.v2.b32 {%0,%1}, [%2];" : "=r"(a), "=r"(b) : "r"(addr) : "memory"); }
__device__ __forceinline__ uint32_t hadd2(uint32_t a, uint32_t b) { uint32_t d; asm("add.rn.bf16x2 %0, %1, %2;" : "=r"(d) : "r"(a), "r"(b)); return d; }
__device__ __forceinline__ uint32_t hfma2(uint32_t a, uint32_t b, uint32_t c) { uint32_t d; asm("fma.rn.bf16x2 %0, %1, %2, %3;" : "=r"(d) : "r"(a), "r"(b), "r"(c)); return d; }
__device__ __forceinline__ uint32_t hmax2(uint32_t a, uint32_t b) { uint32_t d; asm("max.bf16x2 %0, %1, %2;" : "=r"(d) : "r"(a), "r"(b)); return d; }
__device__ __forceinline__ float rcp(float x) { float y; asm("rcp.approx.ftz.f32 %0, %1;" : "=f"(y) : "f"(x)); return y; }
__device__ __forceinline__ float ex2(float x) { float y; asm("ex2.approx.ftz.f32 %0, %1;" : "=f"(y) : "f"(x)); return y; }
__device__ __forceinline__ float gelu_half(float y) {
  float z = y * fmaf(y * y, 8.f * 0.044715f * 0.7978845608028654f, 2.f * 0.7978845608028654f), t;
  asm("tanh.approx.f32 %0, %1;" : "=f"(t) : "f"(z));
  return fmaf(y, t, y);
}
__device__ __forceinline__ void ldsm4(uint32_t addr, uint32_t& a, uint32_t& b, uint32_t& c, uint32_t& d) {
  asm volatile("ldmatrix.sync.aligned.m8n8.x4.shared.b16 {%0,%1,%2,%3}, [%4];" : "=r"(a), "=r"(b), "=r"(c), "=r"(d) : "r"(addr) : "memory");
}

__host__ __device__ constexpr uint32_t q_off(int s) { return ((0xA630u >> (4 * (s & 3))) & 15) * 16 * KB; }
__host__ __device__ constexpr uint32_t g_off(int n) { return (uint32_t)((0x1034210534210534ull >> (4 * n)) & 15) * 32 * KB; }
__host__ __device__ constexpr uint32_t pa_off(int sl) { return (uint32_t)((0x0A181C1410ull >> (8 * sl)) & 255) * 4 * KB; }
__host__ __device__ constexpr uint32_t pb_off(int sl) { return (uint32_t)((0x0500202832ull >> (8 * sl)) & 255) * 4 * KB; }

__device__ __forceinline__ void win_softmax(const float (&S)[3][4], bool e0, bool e1, uint32_t inv0, uint32_t inv1, uint32_t& P0, uint32_t& P1) {
  const uint32_t NEG = 0xCF85u;
  const float L2E = 0.22360679774997896f * 1.4426950408889634f;
  uint32_t A = pack2(e0 ? S[0][0] : S[1][0], e0 ? S[1][2] : S[2][2]);
  uint32_t B = pack2(e1 ? S[0][1] : S[1][1], e1 ? S[1][3] : S[2][3]);
  A = (A & ~inv0) | (NEG & inv0); B = (B & ~inv1) | (NEG & inv1);
  uint32_t m = hmax2(A, B);
  m = hmax2(m, __shfl_xor_sync(0xffffffffu, m, 1));
  m = hmax2(m, __shfl_xor_sync(0xffffffffu, m, 2));
  const float m0 = -bf_lo(m) * L2E, m1 = -bf_hi(m) * L2E;
  P0 = pack2(ex2(fmaf(bf_lo(A), L2E, m0)), ex2(fmaf(bf_lo(B), L2E, m0)));
  P1 = pack2(ex2(fmaf(bf_hi(A), L2E, m1)), ex2(fmaf(bf_hi(B), L2E, m1)));
}

template <bool SMID>
__global__ void __cluster_dims__(2, 1, 1) __launch_bounds__(512, 1)
fused_kernel(const Ptrs pt, const __grid_constant__ Maps mp) {
  extern __shared__ __align__(1024) uint8_t smem_raw[];
  const uint32_t base = smem_u32(smem_raw);
  const uint32_t bars = base + BAR_OFF;
  const int tid = threadIdx.x, lane = tid & 31;
  auto early_pf = [&](int kb) {
    const int c = blockIdx.x & 127;
    const char* p = lane < 16 ? (const char*)pt.x + (c * 16 + lane) * 1280 + kb * 128 : (const char*)pt.wq + kb * 64 * 3840 + (c * 15 + lane - 16) * 128;
    if (lane < 31) asm volatile("prefetch.global.L2 [%0];" ::"l"(p));
  };
  if (tid < 32) early_pf(0);
  {
    if ((tid >> 5) == 8 && elect()) { mbar_init(bars, 1); asm volatile("fence.mbarrier_init.release.cluster;" ::: "memory"); }
    __syncwarp();
    asm volatile("barrier.cluster.arrive.relaxed.aligned;" ::: "memory");
  }
  const int warp = __shfl_sync(0xffffffffu, tid >> 5, 0);
  uint32_t r; asm("mov.u32 %0, %%cluster_ctarank;" : "=r"(r));
  auto BAR = [&](int i) { return bars + i * 8; };
  auto FULL = [&](int s) { return bars + s * 8; };
  auto EMPTY = [&](int s) { return bars + (B_EMPTY + s) * 8; };
  auto DATA = [&](int s) { return bars + (B_DATA + s) * 8; };

  int t;
  if (SMID) { unsigned smid; asm("mov.u32 %0, %%smid;" : "=r"(smid)); t = smid >> 1; }
  else { t = blockIdx.x >> 1; t = t < 4 ? t + 62 : t - 4; }
  if (SMID && (t == 60 || t == 61)) { if (tid == 0) wait_until(clk() + 16000); return; }
  const int u7 = t - 32, q7 = (u7 * 37) >> 8;
  const int g = t < 32 ? (t & 7) : t < 60 ? 1 + u7 - 7 * q7 : 0;
  const int i = t < 32 ? (t >> 3) : t < 60 ? 4 + q7 : t - 58;
  const int qm = g * 2 + r, qj = i;

  auto init_bars = [&]() {
  if (elect()) {
    const int b0 = warp < 8 ? warp + 2 : warp < 10 ? warp - 8 : 76 + 2 * warp;
    if (warp > 12) mbar_init(BAR(95 + warp), 4);
    if (warp != 8) mbar_init(BAR(b0), warp == 12 ? 2 : 1);
    mbar_init(BAR(b0 + (warp < 10 ? B_EMPTY : 1)), (0x4112114444444444ull >> (4 * warp)) & 15);
    asm volatile("fence.mbarrier_init.release.cluster;" ::: "memory");
  }
  __syncwarp();
  asm volatile("barrier.cluster.arrive.relaxed.aligned;" ::: "memory");
  };
  if (warp == 8) {
    if (elect()) {
      mbar_expect_tx(FULL(0), 46 * KB);
      tma3d(base, &mp.x, 0, qm * 64, 0, FULL(0));
      asm volatile("prefetch.tensormap [%0];" ::"l"(&mp.wqm) : "memory");
      asm volatile("prefetch.tensormap [%0];" ::"l"(&mp.wqr) : "memory");
    }
    __syncwarp();
  }
  asm volatile("barrier.cluster.wait.aligned;" ::: "memory");
  if (warp == 8 && elect()) {
    tma3d_mc(base + 16 * KB + r * 16 * KB, &mp.wqm, qj * 80, r * 32, 0, FULL(0));
    tma3d_mc(base + 28 * KB + r * 16 * KB, &mp.wqr, qj * 80 + 64, r * 32, 0, FULL(0));
  }
  const uint32_t t0 = clk();
  if (warp == 8) TSG(6, 0);
  { init_bars(); asm volatile("barrier.cluster.wait.aligned;" ::: "memory"); }
  const bool hasG = g || i < 4;
  const int i3 = (i * 11) >> 5;
  const int gf = g == 0 ? 3 * (i & 3) + 2 : g < 4 ? g * 4 - 4 + (i >> 1) : 3 * g - 12 + i3, gd = g == 0 ? 4 : g < 4 ? (i & 1) : 2 + i - 3 * i3;
  const int pm = g * 2 + (i >> 2), pn = i & 3;

  unsigned* const epp = pt.sc->cnt + (C_EP + g * 16 + i * 2 + r) * 32;
  auto dep_load = [&](int n, int sl, int par) {
    const bool po = n < NPO;
    mbar_expect_tx(DATA(SP + n), po ? 16 * KB : 20 * KB);
    tma2d(base + (po ? pa_off(sl) : pb_off(sl)), po ? &mp.old_ : &mp.uld, (po ? r * 320 : r * 768 - NPO * 64) + n * 64, po ? pm * 128 + par * S_ : pn * 160 + par * D_, DATA(SP + n));
  };
  auto h_load = [&](int n, int par) {
    mbar_expect_tx(DATA(NQ + n), 16 * KB);
    tma3d(base + g_off(n) + 16 * KB, &mp.h, 0, par * S_ + r * 1024 + n * 64, gd * 2, DATA(NQ + n));
  };

  if (warp < 8) {
    asm volatile("setmaxnreg.inc.sync.aligned.u32 216;");
    if (warp == 1) early_pf(1);
    const int wg = warp >> 2, w = warp & 3;
    const bool lead = (tid & 127) == 0;
    const bool keeper = (wg == (int)r);
    const int rho = lane >> 2, q = lane & 3;
    const uint32_t dbase = (base & 0x3FFFF) >> 4, dwg = dbase + wg * (8 * KB >> 4);
    float accG[64];
    const uint32_t dsend = dbase, dkeep = dbase + 512;
    auto g_issue = [&](int n, bool wait = true) {
      if (wait) mbar_wait(FULL(NQ + n));
      TSG(0, 64 + (wg ^ (int)r) * 64 + NQ + n);
      const uint32_t o = g_off(n) >> 4;
      wg_fence();
#pragma unroll
      for (int k = 0; k < 4; k++)
        Wgmma<128, 1, 1, H128, H128>::run(accG, dwg + o + dlo(16 * KB + k * 2048, 8192), dbase + o + dlo(k * 2048, 8192), (n | k) != 0);
      wg_commit();
    };
    auto g_step = [&](int n) {
      g_issue(n);
      wg_wait<1>();
      if (lead) mbar_arrive(EMPTY(NQ + n - 1));
    };
    uint32_t Qp[10][2], Kp[10][2], Vt[10][2];
    {
      float acc[96], acr[24];
      const uint32_t rempty = mapa(EMPTY(0), r ^ 1);
#pragma unroll 1
      for (int s = 0; s < NQ; s++) {
        mbar_wait(FULL(s));
        TSG(0, 64 + (wg ^ (int)r) * 64 + s);
        const uint32_t o = q_off(s) >> 4;
        wg_fence();
#pragma unroll
        for (int k = 0; k < 4; k++) {
          Wgmma<48, 0, 1, H128, H32>::run(acr, dwg + o + dlo(k * 32, 16), dbase + o + dlo(28 * KB + (k >> 1) * 16 * KB + (k & 1) * 512, 1024), (s | k) != 0);
          Wgmma<192, 0, 1, H128, H128>::run(acc, dwg + o + dlo(k * 32, 16), dbase + o + dlo(16 * KB + (k >> 1) * 16 * KB + (k & 1) * 2048, 4096), (s | k) != 0);
        }
        wg_commit();
        wg_wait<1>();
        if (s > 0 && lead) { mbar_arrive(EMPTY(s - 1)); mbar_arrive_remote(rempty + (s - 1) * 8); }
      }
      bar_sync<1, 256>();
      g_issue(0);
      wg_wait<1>();
      reg_fence(acc); reg_fence(acr);
      if (lead) { mbar_arrive(EMPTY(NQ - 1)); mbar_arrive_remote(rempty + (NQ - 1) * 8); }
      TSG(1, 17 + (wg ^ (int)r) * 16);
#pragma unroll
      for (int c = 0; c < 10; c++) {
        const float* ak = c < 8 ? acc + 4 * (8 + c) : acr + 4 * (c - 6);
        const float* av = c < 8 ? acc + 4 * (16 + c) : acr + 4 * (c - 4);
        Kp[c][1] = pack2(ak[2], ak[3]); Vt[c][1] = movm(pack2(av[2], av[3]));
      }
      mbar_wait(EMPTY(7));
      mbar_wait(BAR(B_LNDONE));
      const uint32_t dst = base + HALO_OFF + (w == 3 ? 8 + wg : warp + 1) * 2560;
#pragma unroll
      for (int c = 0; c < 2; c++) {
        sts128(dst + c * 1280 + lane * 16, Kp[5 * c][1], Kp[5 * c + 1][1], Kp[5 * c + 3][1], Kp[5 * c + 4][1]);
        sts128(dst + c * 1280 + 512 + lane * 16, Kp[5 * c + 2][1], Vt[5 * c][1], Vt[5 * c + 1][1], Vt[5 * c + 2][1]);
        sts64(dst + c * 1280 + 1024 + lane * 8, Vt[5 * c + 3][1], Vt[5 * c + 4][1]);
      }
      bar_arrive<8, 288>();
      g_step(1);
#pragma unroll
      for (int c = 0; c < 10; c++) {
        float* aq = c < 8 ? acc + 4 * c : acr + 4 * (c - 8);
        float* ak = c < 8 ? acc + 4 * (8 + c) : acr + 4 * (c - 6);
        float* av = c < 8 ? acc + 4 * (16 + c) : acr + 4 * (c - 4);
        asm volatile("" : "+f"(aq[0]), "+f"(aq[2]), "+f"(ak[0]), "+f"(av[0])::"memory");
        Qp[c][0] = pack2(aq[0], aq[1]); Qp[c][1] = pack2(aq[2], aq[3]);
        Kp[c][0] = pack2(ak[0], ak[1]); Vt[c][0] = movm(pack2(av[0], av[1]));
      }
    }
#pragma unroll 1
    for (int n = 2; n < ATT0; n++) g_step(n);
    mbar_wait(BAR(B_HALO));
    {
      const bool e0 = 2 * q > rho, e1 = 2 * q + 1 > rho, first = (qm == 0 && w == 0), lo = q < 2;
      uint32_t maskE = (e0 ? 0xFFFFu : 0u) | (e1 ? 0xFFFF0000u : 0u);
      uint32_t inv0 = (first && e0) ? 0xFFFFu : 0u, inv1 = (first && e1) ? 0xFFFFu : 0u;
      const uint32_t hsrc = base + HALO_OFF + warp * 2560;
      uint32_t odst = base + OST_OFF + (warp * 16 + (lane & 15)) * 160 + (lane >> 4) * 16;
      uint32_t K0[10], V0[10], Qm[4][2];
#pragma unroll
      for (int c = 0; c < 2; c++) {
        const uint4 a = lds128(hsrc + c * 1280 + lane * 16), b = lds128(hsrc + c * 1280 + 512 + lane * 16);
        K0[5 * c] = a.x; K0[5 * c + 1] = a.y; K0[5 * c + 3] = a.z; K0[5 * c + 4] = a.w;
        K0[5 * c + 2] = b.x; V0[5 * c] = b.y; V0[5 * c + 1] = b.z; V0[5 * c + 2] = b.w;
        lds64(hsrc + c * 1280 + 1024 + lane * 8, V0[5 * c + 3], V0[5 * c + 4]);
      }
#pragma unroll
      for (int h = 0; h < 4; h++) {
        Qm[h][0] = (lo != (h & 1)) ? Qp[5 * (h >> 1) + 2][0] : 0u; Qm[h][1] = (lo != (h & 1)) ? Qp[5 * (h >> 1) + 2][1] : 0u;
        asm volatile("" : "+r"(Qm[h][0]), "+r"(Qm[h][1]));
      }
      asm volatile("" : "+r"(maskE), "+r"(inv0), "+r"(inv1), "+r"(odst));
      wg_wait<0>();
      if (lead) mbar_arrive(EMPTY(NQ + ATT0 - 1));
      mbar_wait(FULL(NQ + ATT0));
      TSG(1, 30 + (wg ^ (int)r) * 16);
      float S[4][3][4], O[4][3][4], sm[4][4];
#pragma unroll
      for (int h = 0; h < 4; h++) {
        const int G = 5 * (h >> 1) + 2, H = G - 2 + 3 * (h & 1);
        mma1688z(S[h][0], Qm[h][0], Qm[h][1], K0[G]); mma1688z(S[h][1], Qm[h][0], Qm[h][1], Kp[G][0]); mma1688z(S[h][2], Qm[h][0], Qm[h][1], Kp[G][1]);
        mma16816(S[h][0], Qp[H][0], Qp[H][1], Qp[H + 1][0], Qp[H + 1][1], K0[H], K0[H + 1]);
        mma16816(S[h][1], Qp[H][0], Qp[H][1], Qp[H + 1][0], Qp[H + 1][1], Kp[H][0], Kp[H + 1][0]);
        mma16816(S[h][2], Qp[H][0], Qp[H][1], Qp[H + 1][0], Qp[H + 1][1], Kp[H][1], Kp[H + 1][1]);
      }
#pragma unroll
      for (int h = 0; h < 4; h++) {
        uint32_t P0, P1;
        win_softmax(S[h], e0, e1, inv0, inv1, P0, P1);
        const int g0 = 5 * (h >> 1) + 2 * (h & 1);
        mma1688z(sm[h], P0, P1, 0x3F803F80u);
#pragma unroll
        for (int c = 0; c < 3; c++) mma1688z(O[h][c], P0 & maskE, 0u, V0[g0 + c]);
#pragma unroll
        for (int c = 0; c < 3; c++) mma16816(O[h][c], P0 & ~maskE, P1 & maskE, 0u, P1 & ~maskE, Vt[g0 + c][0], Vt[g0 + c][1]);
      }
#pragma unroll
      for (int hp = 0; hp < 2; hp++) {
        float (&A)[3][4] = O[2 * hp];
        float (&B)[3][4] = O[2 * hp + 1];
        const float a0 = rcp(sm[2 * hp][0]), a1 = rcp(sm[2 * hp][2]), b0 = rcp(sm[2 * hp + 1][0]), b1 = rcp(sm[2 * hp + 1][2]);
        stsm4(odst + hp * 80, pack2(A[0][0] * a0, A[0][1] * a0), pack2(A[0][2] * a1, A[0][3] * a1), pack2(A[1][0] * a0, A[1][1] * a0), pack2(A[1][2] * a1, A[1][3] * a1));
        stsm4(odst + hp * 80 + 48, pack2(B[1][0] * b0, B[1][1] * b0), pack2(B[1][2] * b1, B[1][3] * b1), pack2(B[2][0] * b0, B[2][1] * b0), pack2(B[2][2] * b1, B[2][3] * b1));
        const float c0 = lo ? a0 : b0, c1 = lo ? a1 : b1;
        stsm2(odst + hp * 80 + 32, pack2((lo ? A[2][0] : B[0][0]) * c0, (lo ? A[2][1] : B[0][1]) * c0), pack2((lo ? A[2][2] : B[0][2]) * c1, (lo ? A[2][3] : B[0][3]) * c1));
      }
      bar_sync<2, 288>();
    }
    TSG(1, 19 + (wg ^ (int)r) * 16);
    g_issue(ATT0, false);
    float3 gt0, gt1;
    uint32_t bb[8];
    mbar_wait(BAR(B_HALL));
    {
      ldsm4(base + B1_OFF + (lane >> 3) * 16, bb[0], bb[1], bb[2], bb[3]);
      ldsm4(base + B1_OFF + 64 + (lane >> 3) * 16, bb[4], bb[5], bb[6], bb[7]);
      const float4* gp = pt.sc->gate + pm * 128 + warp * 16 + rho;
      asm volatile("ld.relaxed.gpu.global.v2.f32 {%0,%1}, [%3];\nld.relaxed.gpu.global.f32 %2, [%3+8];" : "=f"(gt0.x), "=f"(gt0.y), "=f"(gt0.z) : "l"(gp) : "memory");
      asm volatile("ld.relaxed.gpu.global.v2.f32 {%0,%1}, [%3];\nld.relaxed.gpu.global.f32 %2, [%3+8];" : "=f"(gt1.x), "=f"(gt1.y), "=f"(gt1.z) : "l"(gp + 8) : "memory");
    }
#pragma unroll 1
    for (int n = ATT0 + 1; n < NG - LEADG; n++) g_step(n);
    const uint32_t rcv = base + RECV_OFF;
    {
      float accS[32], accK[32];
      mbar_wait(BAR(B_XFREE0));
#pragma unroll
      for (int n = NG - LEADG; n < NG; n++) {
        mbar_wait(FULL(NQ + n));
        TSG(0, 64 + (wg ^ (int)r) * 64 + NQ + n);
        const uint32_t o = g_off(n) >> 4;
        wg_fence();
#pragma unroll
        for (int k = 0; k < 4; k++) Wgmma<64, 1, 1, H128, H128>::run(accS, dwg + o + dlo(16 * KB + k * 2048, 8192), dsend + o + dlo(k * 2048, 8192), n != NG - LEADG || k);
        wg_commit();
        if (n == NG - LEADG) {
          wg_wait<1>(); reg_fence(accG);
          if (lead) mbar_arrive(EMPTY(NQ + n - 1));
        }
      }
      const uint32_t rdst = mapa(rcv + warp * 1024 + lane * 16, r ^ 1), rbar = mapa(BAR(B_RECVG), r ^ 1), half = 0x3F003F00u;
      TSG(2, 20 + (wg ^ (int)r) * 16);
      wg_fence();
#pragma unroll
      for (int e = 0; e < 4 * LEADG; e++) {
        const int n = NG - LEADG + (e >> 2), k = e & 3;
        Wgmma<64, 1, 1, H128, H128>::run(accK, dwg + (g_off(n) >> 4) + dlo(16 * KB + k * 2048, 8192), dkeep + (g_off(n) >> 4) + dlo(k * 2048, 8192), e);
        if (k == 0 || k == 3) wg_commit();
        if (k == 0) {
          wg_wait<1>();
          if (e == 0) reg_fence(accS); else if (lead) mbar_arrive(EMPTY(NQ + n - 1));
        }
        if (e % SDIV == 0 && e / SDIV < 4) {
          const int c = e / SDIV;
          float a[8];
#pragma unroll
          for (int f = 0; f < 8; f++) a[f] = accS[8 * c + f] + accG[8 * c + f];
          const uint32_t h0 = hmul2(bb[2 * c], half), h1 = hmul2(bb[2 * c + 1], half);
          st_async4(rdst + (c >> 1) * 8192 + (c & 1) * 512, hfma2(pack2(a[0], a[1]), half, h0), hfma2(pack2(a[2], a[3]), half, h0),
                    hfma2(pack2(a[4], a[5]), half, h1), hfma2(pack2(a[6], a[7]), half, h1), rbar + (c >> 1) * 8);
        }
      }
      wg_wait<0>();
      reg_fence(accK);
      if (lead) mbar_arrive(EMPTY(SP - 1));
      TSG(2, 21 + (wg ^ (int)r) * 16);
      uint32_t udst = rcv + (warp * 16 + (lane & 15)) * 64 + (((lane >> 4) ^ ((lane >> 1) & 3)) << 4), usrc = rcv + warp * 1024 + lane * 16;
      float a[16];
#pragma unroll
      for (int e = 0; e < 16; e++) a[e] = accK[e] + accG[32 + e];
#pragma unroll
      for (int hf = 0; hf < 2; hf++) {
        mbar_wait(BAR(B_RECVG + hf));
        if (hf == 0) TSG(2, 22 + (wg ^ (int)r) * 16);
        const uint4 v0 = lds128(usrc), v1 = lds128(usrc + 512);
        __syncwarp();
        auto ge = [&](float a0, float a1, uint32_t p) { return pack2(gelu_half(fmaf(a0, 0.5f, bf_lo(p))), gelu_half(fmaf(a1, 0.5f, bf_hi(p)))); };
        stsm4(udst, ge(a[0], a[1], v0.x), ge(a[2], a[3], v0.y), ge(a[4], a[5], v0.z), ge(a[6], a[7], v0.w));
        stsm4(udst ^ 32, ge(a[8], a[9], v1.x), ge(a[10], a[11], v1.y), ge(a[12], a[13], v1.z), ge(a[14], a[15], v1.w));
        asm volatile("bar.arrive %0, 288;" ::"r"(3 + hf) : "memory");
        udst += 8192; usrc += 8192;
#pragma unroll
        for (int e = 0; e < 16; e++) a[e] = accK[16 + e] + accG[48 + e];
      }
    }
    TSG(2, 23 + (wg ^ (int)r) * 16);
    float accA[80];
#pragma unroll 1
    for (int n = 0; n < NPO; n++) {
      mbar_wait(FULL(SP + n));
      TSG(0, 64 + (wg ^ (int)r) * 64 + SP + n);
      const uint32_t a = dwg + (pa_off(n) >> 4), b = dbase + (pb_off(n) >> 4);
      wg_fence();
#pragma unroll
      for (int k = 0; k < 4; k++) Wgmma<160, 0, 1, H128, H64>::run(accA, a + dlo(k * 32, 16), b + dlo(k * 1024, 4096), (n | k) != 0);
      wg_commit();
      wg_wait<1>();
      if (lead && n) mbar_arrive(EMPTY(SP + n - 1));
    }
    TSG(2, 24 + (wg ^ (int)r) * 16);
    float accY[80];
    auto py_mma = [&](int sl, bool acc) {
      const uint32_t a = dwg + (pa_off(sl) >> 4), b = dbase + (pb_off(sl) >> 4);
#pragma unroll
      for (int k = 0; k < 4; k++) Wgmma<160, 1, 0, H128, H128>::run(accY, a + dlo(k * 2048, 8192), b + dlo(k * 32, 16), acc || k != 0);
      wg_commit();
    };
    auto py_step = [&](int n, int sl) {
      mbar_wait(FULL(SP + n));
      TSG(0, 64 + (wg ^ (int)r) * 64 + SP + n);
      wg_fence();
      py_mma(sl, n != NPO);
      if (n == NP - 1) bar_arrive<10, 256>();
      wg_wait<1>();
      if (lead) mbar_arrive(EMPTY(SP + n - 1));
    };
    py_step(NPO, 0);
    reg_fence(accA);
    {
      const float c0 = keeper ? gt0.z : 0.f, c1 = keeper ? gt1.z : 0.f;
#pragma unroll
      for (int e = 0; e < 80; e++) accA[e] = (e & 2) ? fmaf(gt1.x, accA[e], c1) : fmaf(gt0.x, accA[e], c0);
      reg_fence(accA);
    }
    {
      int sl = 1;
#pragma unroll 1
      for (int n = NPO + 1; n < NP - (keeper ? LEADP : 0); n++) {
        py_step(n, sl);
        sl = sl == 4 ? 0 : sl + 1;
      }
    }
    if (keeper) {
      wg_wait<0>();
      if (lead) mbar_arrive(EMPTY(NSTEP - LEADP - 1));
      bar_sync<10, 256>();
      TSG(0, 64 + NSTEP - LEADP);
#pragma unroll 1
      for (int n = NP - LEADP; n < NP; n++) { wg_fence(); py_mma(n < 15 ? n - 10 : n - 15, true); }
    }
    if (!keeper) mbar_wait(BAR(B_XFREE));
    TSG(3, 25 + (wg ^ (int)r) * 16);
    wg_wait<0>();
    reg_fence(accY);
    TSG(3, 26 + (wg ^ (int)r) * 16);
    auto mix = [&](int e) {
      const float om = (e & 1) ? gt1.y : gt0.y;
      return pack2(fmaf(om, accY[2 * e], accA[2 * e]), fmaf(om, accY[2 * e + 1], accA[2 * e + 1]));
    };
    const uint32_t xch = rcv + w * 1024 + lane * 16;
    const uint32_t rdst = mapa(xch, r ^ 1), rbar = mapa(BAR(B_RECVP), r ^ 1);
    const uint32_t odst = base + RECV_OFF + (w * 16 + (lane & 15)) * 64 + (((lane >> 4) ^ ((lane >> 1) & 3)) << 4);
#pragma unroll
    for (int c = 0; c < 5; c++) {
      uint32_t pk[8];
      uint4 v0, v1;
      if (keeper) { mbar_wait(BAR(B_RECVP + c)); v0 = lds128(xch + c * 4096); v1 = lds128(xch + c * 4096 + 512); __syncwarp(); }
      if (c == 0) TSG(3, 27 + (wg ^ (int)r) * 16);
#pragma unroll
      for (int e = 0; e < 8; e++) pk[e] = mix(8 * c + e);
      if (keeper) {
        stsm4(odst + c * 4096, hadd2(pk[0], v0.x), hadd2(pk[1], v0.y), hadd2(pk[2], v0.z), hadd2(pk[3], v0.w));
        stsm4((odst ^ 32) + c * 4096, hadd2(pk[4], v1.x), hadd2(pk[5], v1.y), hadd2(pk[6], v1.z), hadd2(pk[7], v1.w));
        asm volatile("bar.arrive %0, 160;" ::"r"(11 + c) : "memory");
      } else {
        {
          st_async4(rdst + c * 4096, pk[0], pk[1], pk[2], pk[3], rbar + c * 8);
          st_async4(rdst + c * 4096 + 512, pk[4], pk[5], pk[6], pk[7], rbar + c * 8);
        }
      }
    }
    TSG(3, 28 + (wg ^ (int)r) * 16);
  } else if (warp >= 12) {
    asm volatile("setmaxnreg.dec.sync.aligned.u32 48;");
    const int lw = warp - 12;
    const int row = r * 1024 + lw * 64 + g * 8 + i;
    uint2 gw[5], xn[5];
#pragma unroll
    for (int c = 0; c < 5; c++) gw[c] = ldg64((const uint2*)pt.gw + c * 32 + lane);
    const float b2v = __bfloat162float(pt.b2[row + (lane & 3) * 256]);
    const unsigned ep0 = ld_relaxed(epp);
    wait_until(t0 + LNDELAY);
    const uint2* xp = (const uint2*)(pt.x + (size_t)row * D_) + lane;
#pragma unroll 1
    for (int k = -1; k < 4; k++) {
      uint32_t xv[10];
#pragma unroll
      for (int c = 0; c < 5; c++) { xv[2 * c] = xn[c].x; xv[2 * c + 1] = xn[c].y; }
      if (k < 3) {
#pragma unroll
        for (int c = 0; c < 5; c++) xn[c] = ldg64(xp + c * 32);
        xp += 256 * D_ / 4;
      }
      const uint32_t st = base + hst_off(k) + lw * HPITCH;
      if (k >= 0) {
        float s0 = 0.f, s1 = 0.f, q0 = 0.f, q1 = 0.f, z0 = 0.f, z1 = 0.f;
#pragma unroll
        for (int c = 0; c < 10; c++) {
          const float lo = bf_lo(xv[c]), hi = bf_hi(xv[c]);
          const uint32_t p = hmul2(xv[c], (c & 1) ? gw[c >> 1].y : gw[c >> 1].x);
          s0 += lo; s1 += hi; q0 = fmaf(lo, lo, q0); q1 = fmaf(hi, hi, q1); z0 += bf_lo(p); z1 += bf_hi(p);
        }
        float sx = s0 + s1, sq = q0 + q1, sz = z0 + z1;
#pragma unroll
        for (int o = 1; o < 32; o <<= 1) { sx += __shfl_xor_sync(0xffffffffu, sx, o); sq += __shfl_xor_sync(0xffffffffu, sq, o); sz += __shfl_xor_sync(0xffffffffu, sz, o); }
        const float mean = sx * (1.f / D_), var = fmaxf(fmaf(-mean, mean, sq * (1.f / D_)), 0.f);
        float sd;
        asm("sqrt.approx.ftz.f32 %0, %1;" : "=f"(sd) : "f"(bf_round(bf_round(var) + 1e-5f)));
        const float rs = rcp(bf_round(sd)), rh = bf_round(rs);
        const uint32_t r1 = pack2(rh, rh), r2 = pack2(rs - rh, rs - rh), mb = pack2(mean, mean);
        const float gg = bf_round(rcp(1.f + ex2(-1.4426950408889634f * bf_round(sz)))), om = bf_round(1.f - gg);
#pragma unroll
        for (int c = 0; c < 5; c++) {
          const uint32_t a = hsub2(xv[2 * c], mb), b = hsub2(xv[2 * c + 1], mb);
          sts64(st + c * 256 + lane * 8, hfma2(a, r1, hmul2(a, r2)), hfma2(b, r1, hmul2(b, r2)));
        }
        if (lane == k) sts128(base + GST_OFF + (k * 4 + lw) * 16, __float_as_uint(gg), __float_as_uint(om), __float_as_uint(om * b2v), 0);
        __syncwarp();
        if (lane == 0) mbar_arrive(BAR(B_LNROW + k));
      }
    }
    const unsigned ep = __shfl_sync(0xffffffffu, ep0, 0) + 1;
    mbar_wait(FULL(4));
    if (lw == 3) {
      if (elect()) {
        asm volatile("mbarrier.expect_tx.relaxed.cta.shared::cta.b64 [%0], 128;" ::"r"(BAR(B_HALO)) : "memory");
        bulk_ld(base + B1_OFF, pt.b1 + gf * 128 + (r ^ 1) * 64, 128, BAR(B_HALO));
      }
      __syncwarp();
      if (ep == 1) mbar_wait(BAR(B_HALL));
      mbar_wait(EMPTY(NQ + HG));
      TSG(4, 9);
      for (uint32_t par = 0;; par ^= 1) {
        if (elect()) {
          mbar_expect_tx(BAR(B_HDATA), 5120);
          const uint4* src = pt.sc->halo + ((ep & 1) * 136 + qm * 8 + qj) * 320;
          bulk_ld(base + HALO_OFF, src, 2560, BAR(B_HDATA));
          bulk_ld(base + HALO_OFF + 4 * 2560, src + 160, 2560, BAR(B_HDATA));
        }
        __syncwarp();
        mbar_wait_par(BAR(B_HDATA), par);
        const uint32_t a = base + HALO_OFF + min(lane, 19) * 128 + 124;
        if (!__any_sync(0xffffffffu, max(lds32(a), lds32(a + 4 * 2560)) == ~0u)) break;
        __nanosleep(RGAP);
      }
      if (lane == 0) mbar_arrive(BAR(B_HALO));
      TSG(4, 14);
    }
    if (lw == 1 || lw == 2) {
      int sl = lw - 1;
      const uint32_t last = base + lane * 128 + ((lane & 7) ^ 7) * 16 + 12;
#pragma unroll 1
      for (int n = lw - 1 - (hasG ? NG : 0); n < NP; n += 2) {
        const bool po = (unsigned)n < NPO;
        const uint32_t a = last + (po ? pa_off(sl) : n < 0 ? g_off(n + NG) + 16 * KB : pb_off(sl));
        const uint32_t b = po ? a ^ 0x7C : n < 0 ? a : a + 4096;
        for (uint32_t par = 0;; par ^= 1) {
          mbar_wait_par(DATA(SP + n), par);
          uint32_t m = max(max(max(lds32(a), lds32(a + 4096)), max(lds32(a + 8192), lds32(a + 12288))), lds32(b + 12288));
          if (po) m = max(max(m, lds32(b)), max(lds32(b + 4096), lds32(b + 8192)));
          if (!__any_sync(0xffffffffu, m == ~0u)) break;
          __nanosleep(RGAP);
          if (elect()) { if (n < 0) h_load(n + NG, ep & 1); else dep_load(n, sl, ep & 1); }
          __syncwarp();
        }
        if (lane == 0) mbar_arrive(FULL(SP + n));
        if (n >= 0) sl = sl >= 3 ? sl - 3 : sl + 2;
      }
    }
    if (lane == 0) {
      if (lw == 0) {
        int n = 0;
        while (!mbar_try(BAR(B_RECVP + 4))) {
          __nanosleep(100);
          if (++n > (1 << 23)) asm volatile("st.global.u32 [%0], 0;" ::"l"((char*)pt.sc + 1) : "memory");
        }
      }
    }
  } else {
    asm volatile("setmaxnreg.dec.sync.aligned.u32 32;");
    if (warp > 8) {
      unsigned* cnt = pt.sc->cnt;
      const unsigned ep0 = ld_relaxed(epp);
      const bool one = elect();
      if (one) {
#pragma unroll 1
        for (int s = NQ + warp - 9; s < NSTEP + 5; s += 3) { mbar_init(FULL(s), 2); mbar_init(EMPTY(s), 2); mbar_init(DATA(s), 1); }
        if (warp == 11) mbar_init(BAR(B_HDATA), 1);
        fence_async_smem();
      }
      __syncwarp();
      bar_arrive<5, 128>();
      const unsigned ep = __shfl_sync(0xffffffffu, ep0, 0) + 1;
      if (warp == 9) {
        const int row0 = r * 1024 + g * 8 + i;
#pragma unroll 1
        for (int pass = ep == 1 ? 0 : 1; pass < 2; pass++) {
          if (pass) {
            __nv_bfloat16* hp = pt.sc->h + (size_t)((ep & 1) * S_ + row0) * D_;
#pragma unroll 1
            for (int k = 0; k < 4; k++) {
              mbar_wait(BAR(B_LNROW + k));
              if (one) {
                if (k == 1) { bulk_wait0(); sts64(BAR(EPOCH), ep, 0); mbar_arrive(BAR(B_HROW0)); }
                fence_async_smem();
#pragma unroll
                for (int j = 0; j < 4; j++) bulk_st(hp + (k * 4 + j) * 64 * D_, base + hst_off(k) + j * 1280, 1280);
                bulk_commit();
              }
              __syncwarp();
            }
            if (lane < 16) *(uint4*)(pt.sc->gate + row0 + lane * 64) = lds128(base + GST_OFF + lane * 16);
            __syncwarp();
            if (one) {
              bulk_wait0();
              mbar_arrive(BAR(B_LNDONE));
              TSG(4, 0);
              asm volatile("red.release.gpu.global.add.u32 [%0], 1;" ::"l"(cnt + (C_H + (i & 3)) * 32) : "memory");
              TSG(4, 8);
            }
            mbar_wait(FULL(4));
          }
          const int par = (ep ^ pass) & 1;
          const uint4 mark = make_uint4(~0u, ~0u, ~0u, ~0u);
          uint4* po = (uint4*)(pt.sc->o + (size_t)(par * S_ + qm * 128 + (lane >> 2)) * D_ + ((qj * 5 + 4) >> 2) * 64 - 16) + (lane & 3);
          uint4* pu = (uint4*)(pt.sc->u + (size_t)(par * D_ + gd * 128 + (lane >> 1)) * F_ + (gf * 2 + r) * 64 + 48) + (lane & 1);
          uint4* ph = pt.sc->halo + (par * 136 + qm * 8 + qj + 8) * 320 + (lane >> 1) * 8 + 6 + (lane & 1);
          uint4* pg = (uint4*)(pt.sc->h + (size_t)(par * S_ + row0 + (lane >> 1) * 64) * D_) + 6 + (lane & 1);
#pragma unroll 1
          for (int k = 0; k < 8; k++) {
            if (pass) { mbar_wait(EMPTY(PST + k)); __nanosleep(PGAP); }
            po[0] = mark; po[D_] = mark; po += 2 * D_;
            if (hasG) *pu = mark;
            pu += 2 * F_;
            pg[k * 8] = mark;
            if (k < 5) *(k < 3 ? ph + k * 96 : pg + (k + 5) * 8) = mark;
          }
          if (!pass) __threadfence();
          __syncwarp();
        }
        TSG(4, 3);
        *epp = ep;
      }
      else if (warp == 11) {
        mbar_wait(FULL(1));
        if (one) {
          mbar_expect_tx(BAR(B_RECVG), 8 * KB); mbar_expect_tx(BAR(B_RECVG + 1), 8 * KB);
#pragma unroll 1
          for (int k = 0; k < 9; k++) asm volatile("prefetch.tensormap [%0];" ::"l"(&mp.h + k) : "memory");
        }
        mbar_wait(BAR(B_LNDONE));
        __nanosleep(1500);
        while (!__all_sync(0xffffffffu, (int)(ld_acquire(cnt + (C_H + (lane & 3)) * 32) - ep * 32) >= 0)) {}
        asm volatile("fence.proxy.async.global;" ::: "memory");
        if (one) mbar_arrive(BAR(B_HALL));
        TSG(4, 1);
        if (one) {
          mbar_wait(BAR(B_OFREE));
          await(cnt + (C_O + pm * 2 + r) * 32, ep * 4);
          TSG(4, 4);
          int sl = 0; uint32_t tl = t0;
#pragma unroll 1
          for (int n = 0; n < NP; n++) {
            mbar_wait(EMPTY(n < 2 ? 21 : n == 3 ? 23 : n + 21));
            if (n == NPO) { await(cnt + (C_U + r * 2) * 32, ep * 5 * U0); TSG(4, 6); }
            if (n == NPO + U0) mbar_wait(BAR(B_UREADY));
            wait_until(tl + (n < NPO ? PSTAG : USTAG));
            tl = clk();
            dep_load(n, sl, ep & 1);
            sl = sl == 4 ? 0 : sl + 1;
            TSG(5, 192 + SP + n);
          }
        }
      } else {
        if (one) {
          bar_sync<8, 288>();
          fence_async_smem();
          bulk_st(pt.sc->halo + ((ep & 1) * 136 + qm * 8 + qj + 8) * 320, base + HALO_OFF + 8 * 2560, 5120);
          mbar_arrive(BAR(B_HALO));
          TSG(4, 15);
          bar_sync<2, 288>();
          fence_async_smem();
          TSG(4, 7);
          tma3d_st(&mp.ost, qj * 80, qm * 64 + (ep & 1) * 1024, 0, base + OST_OFF);
          bulk_commit(); bulk_wait0();
          hint(cnt + (C_O + qm * 2 + (qj >> 2)) * 32);
          mbar_arrive(BAR(B_OFREE));
          mbar_wait(EMPTY(NQ + 8));
          mbar_arrive_remote(mapa(BAR(B_XFREE0), r ^ 1));
          TSG(4, 10);
#pragma unroll 1
          for (int hf = 0; hf < 2; hf++) {
            asm volatile("bar.sync %0, 288;" ::"r"(3 + hf) : "memory");
            fence_async_smem();
            TSG(4, 11 + hf);
            if (hasG) tma2d_st(&mp.ust, (gf * 2 + r) * 64 + hf * 32, gd * 128 + (ep & 1) * D_, base + RECV_OFF + hf * 8192);
          }
          bulk_commit(); bulk_wait0();
          const int kb = gf * 2 + r, kh = kb >= 12;
          if (hasG) hint(cnt + (C_U + kh * 2 + (kb - kh * 12 >= U0)) * 32);
          TSG(4, 13);
          await(cnt + (C_U + r * 2 + 1) * 32, ep * (60 - 5 * U0));
          mbar_arrive(BAR(B_UREADY));
          TSG(4, 5);
#pragma unroll 1
          for (int c = 0; c < 5; c++) mbar_expect_tx(BAR(B_RECVP + c), 4 * KB);
          mbar_arrive_remote(mapa(BAR(B_XFREE), r ^ 1));
#pragma unroll 1
          for (int c = 0; c < 5; c++) {
            asm volatile("bar.sync %0, 160;" ::"r"(11 + c) : "memory");
            fence_async_smem();
            tma2d_st(&mp.out, pn * 160 + c * 32, pm * 128 + r * 64, base + RECV_OFF + c * 4 * KB);
          }
          bulk_commit();
          asm volatile("cp.async.bulk.wait_group.read 0;" ::: "memory");
          TSG(3, 3);
        }
      }
    } else {
#pragma unroll 1
      for (int s = 1; s < NQ; s++) {
        const uint32_t a = base + q_off(s), b = a + 16 * KB + r * 16 * KB;
        if (s == 4) bar_sync<5, 128>();
        if (s >= 4) mbar_wait(EMPTY(s - 4));
        else wait_until(t0 + s * STAGGER);
        if (elect()) {
          mbar_expect_tx(FULL(s), 46 * KB);
          tma3d(a, &mp.x, s * 64, qm * 64, 0, FULL(s));
          tma3d_mc(b, &mp.wqm, qj * 80, s * 64 + r * 32, 0, FULL(s));
          tma3d_mc(b + 12 * KB, &mp.wqr, qj * 80 + 64, s * 64 + r * 32, 0, FULL(s));
        }
        TSG(5, 192 + s);
      }
      mbar_wait(BAR(B_HROW0));
      const unsigned ep = __shfl_sync(0xffffffffu, lds32(BAR(EPOCH)), 0);
      if (!elect()) return;
      uint32_t tl = t0;
#pragma unroll 1
      for (int n = 0; n < NG; n++) {
        if (ep == 1) mbar_wait(BAR(B_HALL));
        mbar_wait(EMPTY(n + 4 + ((0x50000156u >> (2 * n)) & 3)));
        wait_until(tl + GSTAG);
        tl = clk();
        const uint32_t a = base + g_off(n);
        if (!hasG) { mbar_arrive(FULL(NQ + n)); mbar_arrive(FULL(NQ + n)); continue; }
        h_load(n, ep & 1);
        mbar_expect_tx(FULL(NQ + n), 16 * KB);
        tma2d(a, &mp.w1, gf * 128 + (r ^ 1) * 64, r * 1024 + n * 64, FULL(NQ + n));
        tma2d(a + 8 * KB, &mp.w1, gf * 128 + r * 64, r * 1024 + n * 64, FULL(NQ + n));
        TSG(5, 192 + NQ + n);
      }
      mbar_wait(BAR(B_OFREE));
      int sl = 0;
#pragma unroll 1
      for (int n = 0; n < NP; n++) {
        mbar_wait(EMPTY(n < 3 ? n + 20 : n + 21));
        wait_until(tl + PSTAG);
        tl = clk();
        const bool po = n < NPO;
        mbar_expect_tx(FULL(SP + n), po ? 20 * KB : 16 * KB);
        tma3d(base + (po ? pb_off(sl) : pa_off(sl)), po ? &mp.wo : &mp.w2, 0, (po ? r * 320 : r * 768 - NPO * 64) + n * 64, po ? pn * 5 : pm * 2, FULL(SP + n));
        sl = sl == 4 ? 0 : sl + 1;
      }
    }
  }
}

typedef CUresult (*EncFn)(CUtensorMap*, CUtensorMapDataType, cuuint32_t, void*, const cuuint64_t*, const cuuint64_t*, const cuuint32_t*,
                          const cuuint32_t*, CUtensorMapInterleave, CUtensorMapSwizzle, CUtensorMapL2promotion, CUtensorMapFloatOOBfill);

void mkmap(EncFn enc, CUtensorMap* m, const void* ptr, int rank, cuuint64_t d0, cuuint64_t d1, cuuint64_t d2, cuuint64_t s1, cuuint64_t s2,
           cuuint32_t b0, cuuint32_t b1, cuuint32_t b2, CUtensorMapSwizzle sw) {
  cuuint64_t dims[3] = {d0, d1, d2}, st[2] = {s1, s2};
  cuuint32_t box[3] = {b0, b1, b2}, es[3] = {1, 1, 1};
  enc(m, CU_TENSOR_MAP_DATA_TYPE_BFLOAT16, rank, (void*)ptr, dims, st, box, es, CU_TENSOR_MAP_INTERLEAVE_NONE, sw,
      CU_TENSOR_MAP_L2_PROMOTION_L2_128B, CU_TENSOR_MAP_FLOAT_OOB_FILL_NONE);
}

}

extern "C" void kernel_launch(void* const* d_in, const int* in_sizes, int n_in, void* d_out, int out_size) {
  (void)in_sizes; (void)n_in; (void)out_size;
  const __nv_bfloat16* x = (const __nv_bfloat16*)d_in[0];
  const __nv_bfloat16* wqkv = (const __nv_bfloat16*)d_in[1];
  const __nv_bfloat16* wo = (const __nv_bfloat16*)d_in[2];
  const __nv_bfloat16* w1 = (const __nv_bfloat16*)d_in[4];
  const __nv_bfloat16* w2 = (const __nv_bfloat16*)d_in[6];
  void* fn = nullptr; cudaDriverEntryPointQueryResult qr;
  cudaGetDriverEntryPoint("cuTensorMapEncodeTiled", &fn, cudaEnableDefault, &qr);
  EncFn enc = (EncFn)fn;
  void* psc;
  cudaGetSymbolAddress(&psc, g_sc);
  Scratch* sc = (Scratch*)psc;
  void *ph = sc->h, *po = sc->o, *pu = sc->u;
  const CUtensorMapSwizzle S128 = CU_TENSOR_MAP_SWIZZLE_128B, S64 = CU_TENSOR_MAP_SWIZZLE_64B, S0 = CU_TENSOR_MAP_SWIZZLE_NONE;
  Maps mp;
  mkmap(enc, &mp.x, x, 3, 640, 1024, 2, 2560, 1280, 64, 64, 2, S128);
  mkmap(enc, &mp.wqm, wqkv, 3, 640, 640, 3, 3840, 1280, 64, 32, 3, S128);
  mkmap(enc, &mp.wqr, wqkv, 3, 640, 640, 3, 3840, 1280, 16, 32, 3, CU_TENSOR_MAP_SWIZZLE_32B);
  mkmap(enc, &mp.h, ph, 3, 64, 4096, 10, 1280, 128, 64, 64, 2, S128);
  mkmap(enc, &mp.w1, w1, 2, 1536, 2048, 1, 3072, 0, 64, 64, 1, S128);
  mkmap(enc, &mp.old_, po, 2, 640, 4096, 1, 1280, 0, 64, 128, 1, S128);
  mkmap(enc, &mp.wo, wo, 3, 32, 640, 20, 1280, 64, 32, 64, 5, S64);
  mkmap(enc, &mp.w2, w2, 3, 64, 1536, 32, 4096, 128, 64, 64, 2, S128);
  mkmap(enc, &mp.uld, pu, 2, 1536, 1280, 1, 3072, 0, 64, 160, 1, S128);
  mkmap(enc, &mp.ost, po, 3, 640, 2048, 2, 2560, 1280, 80, 64, 2, S0);
  mkmap(enc, &mp.ust, pu, 2, 1536, 1280, 1, 3072, 0, 32, 128, 1, S64);
  mkmap(enc, &mp.out, d_out, 2, 640, 2048, 1, 1280, 0, 32, 64, 1, S64);
  Ptrs pt;
  pt.sc = sc; pt.x = x; pt.wq = wqkv; pt.b1 = (const __nv_bfloat16*)d_in[5]; pt.b2 = (const __nv_bfloat16*)d_in[7]; pt.gw = (const __nv_bfloat16*)d_in[8];
  int dev = 0, sms = 0;
  cudaGetDevice(&dev);
  cudaDeviceGetAttribute(&sms, cudaDevAttrMultiProcessorCount, dev);
  if (sms == 132) {
    cudaFuncSetAttribute(fused_kernel<true>, cudaFuncAttributeMaxDynamicSharedMemorySize, SMEM_BYTES);
    fused_kernel<true><<<132, 512, SMEM_BYTES, cudaStreamPerThread>>>(pt, mp);
  } else {
    cudaFuncSetAttribute(fused_kernel<false>, cudaFuncAttributeMaxDynamicSharedMemorySize, SMEM_BYTES);
    fused_kernel<false><<<128, 512, SMEM_BYTES, cudaStreamPerThread>>>(pt, mp);
  }
}
```

```cpp
#include <cuda_runtime.h>
#include <cuda_bf16.h>
#include <cuda.h>
#include <stdint.h>
#include <stddef.h>

namespace {

constexpr int S_ = 2048, D_ = 640, F_ = 1536;
constexpr int NQ = 10, NG = 16, NPO = 5, NPY = 12, SP = NQ + NG, NP = NPO + NPY, NSTEP = SP + NP;
constexpr int KB = 1024;
constexpr int RECV_OFF = 180 * KB;
constexpr int HALO_OFF = 200 * KB;
constexpr int OST_OFF = HALO_OFF, GATE_OFF = HALO_OFF + 8 * 2560;
constexpr int HST_OFF0 = 144 * KB, HST_OFF1 = 208 * KB, HPITCH = 1280;
__host__ __device__ constexpr uint32_t hst_off(int k) { return k == 0 ? HST_OFF0 : HST_OFF1 + (k - 1) * 4 * HPITCH; }
constexpr int BAR_OFF = 225 * KB;
constexpr int B1_OFF = BAR_OFF + 1216;
constexpr int GST_OFF = B1_OFF + 128;
constexpr int SMEM_BYTES = 227 * KB;
constexpr int B_EMPTY = 48, B_HREADY = 96  , B_LNDONE = 98, B_XFREE0 = 99, B_HALO = 100, B_HROW0 = 101, B_OFREE = 102, B_UREADY = 103,
              B_RECVG = 104  , B_RECVP = 147  , EPOCH = 113  , B_XFREE = 106, B_LNROW = 107  , B_DATA = 114 - NQ  ;
#define LEADG 2
#define PSTAG 400
#define PST 31
#define U0 1
#define LNDELAY 1200
#define AV1 1
#define PFN 5
#define HSLP 600
#define EARV 0
#define PEEL 0
#define HG 3
#define RGAP 200
#define USTAG 400
#define SDIV 2
constexpr int LEADP = 4;
#define STAGGER 750
#define ATT0 8

struct Maps { CUtensorMap x, wqm, wqr, h, w1, old_, wo, w2, uld, ost, ust, out; };
struct Scratch {
  __nv_bfloat16 h[S_ * D_], o[2 * S_ * D_], u[2 * D_ * F_];
  uint4 halo[2 * 136 * 320];
  float4 gate[2 * S_];
  unsigned cnt[(8 + 4 + 128) * 32];
};
constexpr int C_H = 0, C_U = 8, C_EP = 12;
struct Ptrs { Scratch* sc; const __nv_bfloat16 *x, *wq, *gw, *b1, *b2, *wo, *w1; };
__device__ __align__(1024) Scratch g_sc;
#define TSG(grp, i)

__device__ __forceinline__ uint32_t clk() { uint32_t c; asm volatile("mov.u32 %0, %%clock;" : "=r"(c)); return c; }
__device__ __forceinline__ void wait_until(uint32_t t) { while ((int)(clk() - t) < 0) {} }
template <int N, int TA, int TB, uint32_t HA, uint32_t HB> struct Wgmma;
template <int TA, int TB, uint32_t HA, uint32_t HB> struct Wgmma<48, TA, TB, HA, HB> {
  static __device__ __forceinline__ void run(float (&d)[24], uint32_t la, uint32_t lb, int sd) {
    asm volatile("{\n.reg .pred p;\n.reg .b64 da, db;\nsetp.ne.b32 p, %26, 0;\nmov.b64 da, {%24, %29};\nmov.b64 db, {%25, %30};\n"
      "wgmma.mma_async.sync.aligned.m64n48k16.f32.bf16.bf16 {%0, %1, %2, %3, %4, %5, %6, %7, %8, %9, %10, %11, %12, %13, %14, %15, %16, %17, %18, %19, %20, %21, %22, %23}, da, db, p, 1, 1, %27, %28;\n}\n"
      : "+f"(d[0]), "+f"(d[1]), "+f"(d[2]), "+f"(d[3]), "+f"(d[4]), "+f"(d[5]), "+f"(d[6]), "+f"(d[7]), "+f"(d[8]), "+f"(d[9]), "+f"(d[10]), "+f"(d[11]), "+f"(d[12]), "+f"(d[13]), "+f"(d[14]), "+f"(d[15]), "+f"(d[16]), "+f"(d[17]), "+f"(d[18]), "+f"(d[19]), "+f"(d[20]), "+f"(d[21]), "+f"(d[22]), "+f"(d[23])
      : "r"(la), "r"(lb), "r"(sd), "n"(TA), "n"(TB), "n"(HA), "n"(HB));
  }
};
template <int TA, int TB, uint32_t HA, uint32_t HB> struct Wgmma<64, TA, TB, HA, HB> {
  static __device__ __forceinline__ void run(float (&d)[32], uint32_t la, uint32_t lb, int sd) {
    asm volatile("{\n.reg .pred p;\n.reg .b64 da, db;\nsetp.ne.b32 p, %34, 0;\nmov.b64 da, {%32, %37};\nmov.b64 db, {%33, %38};\n"
      "wgmma.mma_async.sync.aligned.m64n64k16.f32.bf16.bf16 {%0, %1, %2, %3, %4, %5, %6, %7, %8, %9, %10, %11, %12, %13, %14, %15, %16, %17, %18, %19, %20, %21, %22, %23, %24, %25, %26, %27, %28, %29, %30, %31}, da, db, p, 1, 1, %35, %36;\n}\n"
      : "+f"(d[0]), "+f"(d[1]), "+f"(d[2]), "+f"(d[3]), "+f"(d[4]), "+f"(d[5]), "+f"(d[6]), "+f"(d[7]), "+f"(d[8]), "+f"(d[9]), "+f"(d[10]), "+f"(d[11]), "+f"(d[12]), "+f"(d[13]), "+f"(d[14]), "+f"(d[15]), "+f"(d[16]), "+f"(d[17]), "+f"(d[18]), "+f"(d[19]), "+f"(d[20]), "+f"(d[21]), "+f"(d[22]), "+f"(d[23]), "+f"(d[24]), "+f"(d[25]), "+f"(d[26]), "+f"(d[27]), "+f"(d[28]), "+f"(d[29]), "+f"(d[30]), "+f"(d[31])
      : "r"(la), "r"(lb), "r"(sd), "n"(TA), "n"(TB), "n"(HA), "n"(HB));
  }
};
template <int TA, int TB, uint32_t HA, uint32_t HB> struct Wgmma<128, TA, TB, HA, HB> {
  static __device__ __forceinline__ void run(float (&d)[64], uint32_t la, uint32_t lb, int sd) {
    asm volatile("{\n.reg .pred p;\n.reg .b64 da, db;\nsetp.ne.b32 p, %66, 0;\nmov.b64 da, {%64, %69};\nmov.b64 db, {%65, %70};\n"
      "wgmma.mma_async.sync.aligned.m64n128k16.f32.bf16.bf16 {%0, %1, %2, %3, %4, %5, %6, %7, %8, %9, %10, %11, %12, %13, %14, %15, %16, %17, %18, %19, %20, %21, %22, %23, %24, %25, %26, %27, %28, %29, %30, %31, %32, %33, %34, %35, %36, %37, %38, %39, %40, %41, %42, %43, %44, %45, %46, %47, %48, %49, %50, %51, %52, %53, %54, %55, %56, %57, %58, %59, %60, %61, %62, %63}, da, db, p, 1, 1, %67, %68;\n}\n"
      : "+f"(d[0]), "+f"(d[1]), "+f"(d[2]), "+f"(d[3]), "+f"(d[4]), "+f"(d[5]), "+f"(d[6]), "+f"(d[7]), "+f"(d[8]), "+f"(d[9]), "+f"(d[10]), "+f"(d[11]), "+f"(d[12]), "+f"(d[13]), "+f"(d[14]), "+f"(d[15]), "+f"(d[16]), "+f"(d[17]), "+f"(d[18]), "+f"(d[19]), "+f"(d[20]), "+f"(d[21]), "+f"(d[22]), "+f"(d[23]), "+f"(d[24]), "+f"(d[25]), "+f"(d[26]), "+f"(d[27]), "+f"(d[28]), "+f"(d[29]), "+f"(d[30]), "+f"(d[31]), "+f"(d[32]), "+f"(d[33]), "+f"(d[34]), "+f"(d[35]), "+f"(d[36]), "+f"(d[37]), "+f"(d[38]), "+f"(d[39]), "+f"(d[40]), "+f"(d[41]), "+f"(d[42]), "+f"(d[43]), "+f"(d[44]), "+f"(d[45]), "+f"(d[46]), "+f"(d[47]), "+f"(d[48]), "+f"(d[49]), "+f"(d[50]), "+f"(d[51]), "+f"(d[52]), "+f"(d[53]), "+f"(d[54]), "+f"(d[55]), "+f"(d[56]), "+f"(d[57]), "+f"(d[58]), "+f"(d[59]), "+f"(d[60]), "+f"(d[61]), "+f"(d[62]), "+f"(d[63])
      : "r"(la), "r"(lb), "r"(sd), "n"(TA), "n"(TB), "n"(HA), "n"(HB));
  }
};
template <int TA, int TB, uint32_t HA, uint32_t HB> struct Wgmma<160, TA, TB, HA, HB> {
  static __device__ __forceinline__ void run(float (&d)[80], uint32_t la, uint32_t lb, int sd) {
    asm volatile("{\n.reg .pred p;\n.reg .b64 da, db;\nsetp.ne.b32 p, %82, 0;\nmov.b64 da, {%80, %85};\nmov.b64 db, {%81, %86};\n"
      "wgmma.mma_async.sync.aligned.m64n160k16.f32.bf16.bf16 {%0, %1, %2, %3, %4, %5, %6, %7, %8, %9, %10, %11, %12, %13, %14, %15, %16, %17, %18, %19, %20, %21, %22, %23, %24, %25, %26, %27, %28, %29, %30, %31, %32, %33, %34, %35, %36, %37, %38, %39, %40, %41, %42, %43, %44, %45, %46, %47, %48, %49, %50, %51, %52, %53, %54, %55, %56, %57, %58, %59, %60, %61, %62, %63, %64, %65, %66, %67, %68, %69, %70, %71, %72, %73, %74, %75, %76, %77, %78, %79}, da, db, p, 1, 1, %83, %84;\n}\n"
      : "+f"(d[0]), "+f"(d[1]), "+f"(d[2]), "+f"(d[3]), "+f"(d[4]), "+f"(d[5]), "+f"(d[6]), "+f"(d[7]), "+f"(d[8]), "+f"(d[9]), "+f"(d[10]), "+f"(d[11]), "+f"(d[12]), "+f"(d[13]), "+f"(d[14]), "+f"(d[15]), "+f"(d[16]), "+f"(d[17]), "+f"(d[18]), "+f"(d[19]), "+f"(d[20]), "+f"(d[21]), "+f"(d[22]), "+f"(d[23]), "+f"(d[24]), "+f"(d[25]), "+f"(d[26]), "+f"(d[27]), "+f"(d[28]), "+f"(d[29]), "+f"(d[30]), "+f"(d[31]), "+f"(d[32]), "+f"(d[33]), "+f"(d[34]), "+f"(d[35]), "+f"(d[36]), "+f"(d[37]), "+f"(d[38]), "+f"(d[39]), "+f"(d[40]), "+f"(d[41]), "+f"(d[42]), "+f"(d[43]), "+f"(d[44]), "+f"(d[45]), "+f"(d[46]), "+f"(d[47]), "+f"(d[48]), "+f"(d[49]), "+f"(d[50]), "+f"(d[51]), "+f"(d[52]), "+f"(d[53]), "+f"(d[54]), "+f"(d[55]), "+f"(d[56]), "+f"(d[57]), "+f"(d[58]), "+f"(d[59]), "+f"(d[60]), "+f"(d[61]), "+f"(d[62]), "+f"(d[63]), "+f"(d[64]), "+f"(d[65]), "+f"(d[66]), "+f"(d[67]), "+f"(d[68]), "+f"(d[69]), "+f"(d[70]), "+f"(d[71]), "+f"(d[72]), "+f"(d[73]), "+f"(d[74]), "+f"(d[75]), "+f"(d[76]), "+f"(d[77]), "+f"(d[78]), "+f"(d[79])
      : "r"(la), "r"(lb), "r"(sd), "n"(TA), "n"(TB), "n"(HA), "n"(HB));
  }
};
template <int TA, int TB, uint32_t HA, uint32_t HB> struct Wgmma<192, TA, TB, HA, HB> {
  static __device__ __forceinline__ void run(float (&d)[96], uint32_t la, uint32_t lb, int sd) {
    asm volatile("{\n.reg .pred p;\n.reg .b64 da, db;\nsetp.ne.b32 p, %98, 0;\nmov.b64 da, {%96, %101};\nmov.b64 db, {%97, %102};\n"
      "wgmma.mma_async.sync.aligned.m64n192k16.f32.bf16.bf16 {%0, %1, %2, %3, %4, %5, %6, %7, %8, %9, %10, %11, %12, %13, %14, %15, %16, %17, %18, %19, %20, %21, %22, %23, %24, %25, %26, %27, %28, %29, %30, %31, %32, %33, %34, %35, %36, %37, %38, %39, %40, %41, %42, %43, %44, %45, %46, %47, %48, %49, %50, %51, %52, %53, %54, %55, %56, %57, %58, %59, %60, %61, %62, %63, %64, %65, %66, %67, %68, %69, %70, %71, %72, %73, %74, %75, %76, %77, %78, %79, %80, %81, %82, %83, %84, %85, %86, %87, %88, %89, %90, %91, %92, %93, %94, %95}, da, db, p, 1, 1, %99, %100;\n}\n"
      : "+f"(d[0]), "+f"(d[1]), "+f"(d[2]), "+f"(d[3]), "+f"(d[4]), "+f"(d[5]), "+f"(d[6]), "+f"(d[7]), "+f"(d[8]), "+f"(d[9]), "+f"(d[10]), "+f"(d[11]), "+f"(d[12]), "+f"(d[13]), "+f"(d[14]), "+f"(d[15]), "+f"(d[16]), "+f"(d[17]), "+f"(d[18]), "+f"(d[19]), "+f"(d[20]), "+f"(d[21]), "+f"(d[22]), "+f"(d[23]), "+f"(d[24]), "+f"(d[25]), "+f"(d[26]), "+f"(d[27]), "+f"(d[28]), "+f"(d[29]), "+f"(d[30]), "+f"(d[31]), "+f"(d[32]), "+f"(d[33]), "+f"(d[34]), "+f"(d[35]), "+f"(d[36]), "+f"(d[37]), "+f"(d[38]), "+f"(d[39]), "+f"(d[40]), "+f"(d[41]), "+f"(d[42]), "+f"(d[43]), "+f"(d[44]), "+f"(d[45]), "+f"(d[46]), "+f"(d[47]), "+f"(d[48]), "+f"(d[49]), "+f"(d[50]), "+f"(d[51]), "+f"(d[52]), "+f"(d[53]), "+f"(d[54]), "+f"(d[55]), "+f"(d[56]), "+f"(d[57]), "+f"(d[58]), "+f"(d[59]), "+f"(d[60]), "+f"(d[61]), "+f"(d[62]), "+f"(d[63]), "+f"(d[64]), "+f"(d[65]), "+f"(d[66]), "+f"(d[67]), "+f"(d[68]), "+f"(d[69]), "+f"(d[70]), "+f"(d[71]), "+f"(d[72]), "+f"(d[73]), "+f"(d[74]), "+f"(d[75]), "+f"(d[76]), "+f"(d[77]), "+f"(d[78]), "+f"(d[79]), "+f"(d[80]), "+f"(d[81]), "+f"(d[82]), "+f"(d[83]), "+f"(d[84]), "+f"(d[85]), "+f"(d[86]), "+f"(d[87]), "+f"(d[88]), "+f"(d[89]), "+f"(d[90]), "+f"(d[91]), "+f"(d[92]), "+f"(d[93]), "+f"(d[94]), "+f"(d[95])
      : "r"(la), "r"(lb), "r"(sd), "n"(TA), "n"(TB), "n"(HA), "n"(HB));
  }
};

__device__ __forceinline__ uint32_t smem_u32(const void* p) { return (uint32_t)__cvta_generic_to_shared(p); }
__device__ __forceinline__ void mbar_init(uint32_t bar, int cnt) { asm volatile("mbarrier.init.shared::cta.b64 [%0], %1;" ::"r"(bar), "r"(cnt) : "memory"); }
__device__ __forceinline__ void mbar_expect_tx(uint32_t bar, uint32_t bytes) { asm volatile("mbarrier.arrive.expect_tx.shared::cta.b64 _, [%0], %1;" ::"r"(bar), "r"(bytes) : "memory"); }
__device__ __forceinline__ void mbar_arrive(uint32_t bar) { asm volatile("mbarrier.arrive.shared::cta.b64 _, [%0];" ::"r"(bar) : "memory"); }
__device__ __forceinline__ uint32_t mapa(uint32_t a, uint32_t cta) { uint32_t r; asm("mapa.shared::cluster.u32 %0, %1, %2;" : "=r"(r) : "r"(a), "r"(cta)); return r; }
__device__ __forceinline__ void mbar_arrive_remote(uint32_t rbar) { asm volatile("mbarrier.arrive.shared::cluster.b64 _, [%0];" ::"r"(rbar) : "memory"); }
__device__ __forceinline__ void mbar_wait(uint32_t bar) {
  asm volatile("{\n.reg .pred p;\nW_LOOP:\nmbarrier.try_wait.parity.shared::cta.b64 p, [%0], 0;\n@!p bra.uni W_LOOP;\n}" ::"r"(bar) : "memory");
}
__device__ __forceinline__ void mbar_wait_par(uint32_t bar, uint32_t par) {
  asm volatile("{\n.reg .pred p;\nC_LOOP:\nmbarrier.try_wait.parity.shared::cta.b64 p, [%0], %1;\n@!p bra.uni C_LOOP;\n}" ::"r"(bar), "r"(par) : "memory");
}
__device__ __forceinline__ uint32_t lds32(uint32_t a) { uint32_t v; asm volatile("ld.shared.u32 %0, [%1];" : "=r"(v) : "r"(a) : "memory"); return v; }
__device__ __forceinline__ bool mbar_try(uint32_t bar) {
  uint32_t ok;
  asm volatile("{\n.reg .pred p;\nmbarrier.test_wait.parity.shared::cta.b64 p, [%1], 0;\nselp.b32 %0, 1, 0, p;\n}" : "=r"(ok) : "r"(bar) : "memory");
  return ok;
}
__device__ __forceinline__ bool elect() {
  uint32_t ok;
  asm volatile("{\n.reg .pred p;\nelect.sync _|p, 0xffffffff;\nselp.b32 %0, 1, 0, p;\n}" : "=r"(ok));
  return ok;
}
__device__ __forceinline__ void tma2d(uint32_t dst, const CUtensorMap* m, int c0, int c1, uint32_t bar) {
  asm volatile("cp.async.bulk.tensor.2d.shared::cluster.global.mbarrier::complete_tx::bytes [%0], [%1, {%3,%4}], [%2];" ::"r"(dst), "l"(m), "r"(bar), "r"(c0), "r"(c1) : "memory");
}
__device__ __forceinline__ void tma3d(uint32_t dst, const CUtensorMap* m, int c0, int c1, int c2, uint32_t bar) {
  asm volatile("cp.async.bulk.tensor.3d.shared::cluster.global.mbarrier::complete_tx::bytes [%0], [%1, {%3,%4,%5}], [%2];" ::"r"(dst), "l"(m), "r"(bar), "r"(c0), "r"(c1), "r"(c2) : "memory");
}
__device__ __forceinline__ void tma3d_mc(uint32_t dst, const CUtensorMap* m, int c0, int c1, int c2, uint32_t bar) {
  asm volatile("cp.async.bulk.tensor.3d.shared::cluster.global.mbarrier::complete_tx::bytes.multicast::cluster [%0], [%1, {%3,%4,%5}], [%2], %6;" ::"r"(dst), "l"(m), "r"(bar), "r"(c0), "r"(c1), "r"(c2), "h"((uint16_t)3) : "memory");
}
__device__ __forceinline__ void tma2d_st(const CUtensorMap* m, int c0, int c1, uint32_t src) {
  asm volatile("cp.async.bulk.tensor.2d.global.shared::cta.bulk_group [%0, {%2,%3}], [%1];" ::"l"(m), "r"(src), "r"(c0), "r"(c1) : "memory");
}
__device__ __forceinline__ void tma3d_st(const CUtensorMap* m, int c0, int c1, int c2, uint32_t src) {
  asm volatile("cp.async.bulk.tensor.3d.global.shared::cta.bulk_group [%0, {%2,%3,%4}], [%1];" ::"l"(m), "r"(src), "r"(c0), "r"(c1), "r"(c2) : "memory");
}
__device__ __forceinline__ void bulk_commit() { asm volatile("cp.async.bulk.commit_group;" ::: "memory"); }
__device__ __forceinline__ void bulk_wait0() { asm volatile("cp.async.bulk.wait_group 0;" ::: "memory"); }
__device__ __forceinline__ void fence_async_smem() { asm volatile("fence.proxy.async.shared::cta;" ::: "memory"); }
__device__ __forceinline__ void wg_fence() { asm volatile("wgmma.fence.sync.aligned;" ::: "memory"); }
__device__ __forceinline__ void wg_commit() { asm volatile("wgmma.commit_group.sync.aligned;" ::: "memory"); }
template <int N> __device__ __forceinline__ void wg_wait() { asm volatile("wgmma.wait_group.sync.aligned %0;" ::"n"(N) : "memory"); }
template <int N> __device__ __forceinline__ void reg_fence(float (&a)[N]) {
#pragma unroll
  for (int i = 0; i < N; i++) asm volatile("" : "+f"(a[i])::"memory");
}
template <int ID, int N> __device__ __forceinline__ void bar_sync() { asm volatile("bar.sync %0, %1;" ::"n"(ID), "n"(N) : "memory"); }
template <int ID, int N> __device__ __forceinline__ void bar_arrive() { asm volatile("bar.arrive %0, %1;" ::"n"(ID), "n"(N) : "memory"); }
__host__ __device__ constexpr uint32_t dlo(uint32_t off, uint32_t lbo) { return (off >> 4) | ((lbo >> 4) << 16); }
__host__ __device__ constexpr uint32_t dhi(uint32_t sbo, uint32_t swz) { return (sbo >> 4) | (swz << 30); }
constexpr uint32_t H128 = dhi(1024, 1), H64 = dhi(512, 2), H32 = dhi(256, 3);
__device__ __forceinline__ uint32_t pack2(float lo, float hi) { uint32_t r; asm("cvt.rn.bf16x2.f32 %0, %1, %2;" : "=r"(r) : "f"(hi), "f"(lo)); return r; }
__device__ __forceinline__ float bf_lo(uint32_t v) { return __uint_as_float(v << 16); }
__device__ __forceinline__ float bf_hi(uint32_t v) { return __uint_as_float(v & 0xFFFF0000u); }
__device__ __forceinline__ float bf_round(float v) { return __bfloat162float(__float2bfloat16_rn(v)); }
__device__ __forceinline__ uint32_t movm(uint32_t a) { uint32_t d; asm volatile("movmatrix.sync.aligned.m8n8.trans.b16 %0, %1;" : "=r"(d) : "r"(a)); return d; }
__device__ __forceinline__ void stsm4(uint32_t addr, uint32_t a, uint32_t b, uint32_t c, uint32_t d) {
  asm volatile("stmatrix.sync.aligned.m8n8.x4.shared.b16 [%0], {%1,%2,%3,%4};" ::"r"(addr), "r"(a), "r"(b), "r"(c), "r"(d) : "memory");
}
__device__ __forceinline__ void stsm2(uint32_t addr, uint32_t a, uint32_t b) {
  asm volatile("stmatrix.sync.aligned.m8n8.x2.shared.b16 [%0], {%1,%2};" ::"r"(addr), "r"(a), "r"(b) : "memory");
}
__device__ __forceinline__ void sts128(uint32_t addr, uint32_t a, uint32_t b, uint32_t c, uint32_t d) {
  asm volatile("st.shared.v4.b32 [%0], {%1,%2,%3,%4};" ::"r"(addr), "r"(a), "r"(b), "r"(c), "r"(d) : "memory");
}
__device__ __forceinline__ void sts64(uint32_t addr, uint32_t a, uint32_t b) { asm volatile("st.shared.v2.b32 [%0], {%1,%2};" ::"r"(addr), "r"(a), "r"(b) : "memory"); }
__device__ __forceinline__ uint4 lds128(uint32_t addr) { uint4 v; asm volatile("ld.shared.v4.b32 {%0,%1,%2,%3}, [%4];" : "=r"(v.x), "=r"(v.y), "=r"(v.z), "=r"(v.w) : "r"(addr) : "memory"); return v; }
__device__ __forceinline__ uint32_t hmul2(uint32_t a, uint32_t b) { uint32_t d; asm("mul.rn.bf16x2 %0, %1, %2;" : "=r"(d) : "r"(a), "r"(b)); return d; }
__device__ __forceinline__ uint32_t hsub2(uint32_t a, uint32_t b) { uint32_t d; asm("sub.rn.bf16x2 %0, %1, %2;" : "=r"(d) : "r"(a), "r"(b)); return d; }
__device__ __forceinline__ void mma16816(float (&c)[4], uint32_t a0, uint32_t a1, uint32_t a2, uint32_t a3, uint32_t b0, uint32_t b1) {
  asm volatile("mma.sync.aligned.m16n8k16.row.col.f32.bf16.bf16.f32 {%0,%1,%2,%3}, {%4,%5,%6,%7}, {%8,%9}, {%0,%1,%2,%3};"
               : "+f"(c[0]), "+f"(c[1]), "+f"(c[2]), "+f"(c[3]) : "r"(a0), "r"(a1), "r"(a2), "r"(a3), "r"(b0), "r"(b1));
}
__device__ __forceinline__ void mma1688z(float (&c)[4], uint32_t a0, uint32_t a1, uint32_t b0, float c0 = 0.f) {
  asm volatile("mma.sync.aligned.m16n8k8.row.col.f32.bf16.bf16.f32 {%0,%1,%2,%3}, {%4,%5}, {%6}, {%7,%7,%7,%7};"
               : "=f"(c[0]), "=f"(c[1]), "=f"(c[2]), "=f"(c[3]) : "r"(a0), "r"(a1), "r"(b0), "f"(c0));
}
__device__ __forceinline__ unsigned ld_relaxed(const unsigned* p) { unsigned v; asm volatile("ld.relaxed.gpu.global.u32 %0, [%1];" : "=r"(v) : "l"(p) : "memory"); return v; }
__device__ __forceinline__ unsigned ld_acquire(const unsigned* p) { unsigned v; asm volatile("ld.acquire.gpu.global.u32 %0, [%1];" : "=r"(v) : "l"(p) : "memory"); return v; }
__device__ __forceinline__ void hint(unsigned* p) { asm volatile("red.relaxed.gpu.global.add.u32 [%0], 1;" ::"l"(p) : "memory"); }
__device__ __forceinline__ void await(const unsigned* p, unsigned target) { while ((int)(ld_relaxed(p) - target) < 0) {} }
__device__ __forceinline__ void bulk_st(void* g, uint32_t src, uint32_t bytes) {
  asm volatile("cp.async.bulk.global.shared::cta.bulk_group [%0], [%1], %2;" ::"l"(g), "r"(src), "r"(bytes) : "memory");
}
__device__ __forceinline__ void bulk_ld(uint32_t dst, const void* g, uint32_t bytes, uint32_t bar) {
  asm volatile("cp.async.bulk.shared::cluster.global.mbarrier::complete_tx::bytes [%0], [%1], %2, [%3];" ::"r"(dst), "l"(g), "r"(bytes), "r"(bar) : "memory");
}
__device__ __forceinline__ uint2 ldg64(const uint2* p) { uint2 v; asm volatile("ld.global.nc.v2.u32 {%0,%1}, [%2];" : "=r"(v.x), "=r"(v.y) : "l"(p)); return v; }
__device__ __forceinline__ void st_async4(uint32_t raddr, uint32_t a, uint32_t b, uint32_t c, uint32_t d, uint32_t rbar) {
  asm volatile("st.async.weak.shared::cluster.mbarrier::complete_tx::bytes.v4.b32 [%0], {%1,%2,%3,%4}, [%5];" ::"r"(raddr), "r"(a), "r"(b), "r"(c), "r"(d), "r"(rbar) : "memory");
}
__device__ __forceinline__ void lds64(uint32_t addr, uint32_t& a, uint32_t& b) { asm volatile("ld.shared.v2.b32 {%0,%1}, [%2];" : "=r"(a), "=r"(b) : "r"(addr) : "memory"); }
__device__ __forceinline__ uint32_t hadd2(uint32_t a, uint32_t b) { uint32_t d; asm("add.rn.bf16x2 %0, %1, %2;" : "=r"(d) : "r"(a), "r"(b)); return d; }
__device__ __forceinline__ uint32_t hfma2(uint32_t a, uint32_t b, uint32_t c) { uint32_t d; asm("fma.rn.bf16x2 %0, %1, %2, %3;" : "=r"(d) : "r"(a), "r"(b), "r"(c)); return d; }
__device__ __forceinline__ uint32_t hmax2(uint32_t a, uint32_t b) { uint32_t d; asm("max.bf16x2 %0, %1, %2;" : "=r"(d) : "r"(a), "r"(b)); return d; }
__device__ __forceinline__ float rcp(float x) { float y; asm("rcp.approx.ftz.f32 %0, %1;" : "=f"(y) : "f"(x)); return y; }
__device__ __forceinline__ float ex2(float x) { float y; asm("ex2.approx.ftz.f32 %0, %1;" : "=f"(y) : "f"(x)); return y; }
__device__ __forceinline__ float gelu_half(float y) {
  float z = y * fmaf(y * y, 8.f * 0.044715f * 0.7978845608028654f, 2.f * 0.7978845608028654f), t;
  asm("tanh.approx.f32 %0, %1;" : "=f"(t) : "f"(z));
  return fmaf(y, t, y);
}
__device__ __forceinline__ void ldsm4(uint32_t addr, uint32_t& a, uint32_t& b, uint32_t& c, uint32_t& d) {
  asm volatile("ldmatrix.sync.aligned.m8n8.x4.shared.b16 {%0,%1,%2,%3}, [%4];" : "=r"(a), "=r"(b), "=r"(c), "=r"(d) : "r"(addr) : "memory");
}

__host__ __device__ constexpr uint32_t q_off(int s) { return ((0xA630u >> (4 * (s & 3))) & 15) * 16 * KB; }
__host__ __device__ constexpr uint32_t g_off(int n) { return (uint32_t)((0x1034210534210534ull >> (4 * n)) & 15) * 32 * KB; }
__host__ __device__ constexpr uint32_t pa_off(int sl) { return (uint32_t)((0x0A181C1410ull >> (8 * sl)) & 255) * 4 * KB; }
__host__ __device__ constexpr uint32_t pb_off(int sl) { return (uint32_t)((0x0500202832ull >> (8 * sl)) & 255) * 4 * KB; }

__device__ __forceinline__ void win_softmax(const float (&S)[3][4], bool e0, bool e1, uint32_t& P0, uint32_t& P1) {
  const float L2E = 1.4426950408889634f;
  auto scaled = [](uint32_t v) { return hfma2(v, 0x3E653E65u, hmul2(v, 0xB7DAB7DAu)); };
  const uint32_t A = scaled(pack2(e0 ? S[0][0] : S[1][0], e0 ? S[1][2] : S[2][2]));
  const uint32_t B = scaled(pack2(e1 ? S[0][1] : S[1][1], e1 ? S[1][3] : S[2][3]));
  uint32_t m = hmax2(A, B);
  m = hmax2(m, __shfl_xor_sync(0xffffffffu, m, 1));
  m = hmax2(m, __shfl_xor_sync(0xffffffffu, m, 2));
  const float m0 = -bf_lo(m) * L2E, m1 = -bf_hi(m) * L2E;
  P0 = pack2(ex2(fmaf(bf_lo(A), L2E, m0)), ex2(fmaf(bf_lo(B), L2E, m0)));
  P1 = pack2(ex2(fmaf(bf_hi(A), L2E, m1)), ex2(fmaf(bf_hi(B), L2E, m1)));
}

__global__ void __cluster_dims__(2, 1, 1) __launch_bounds__(512, 1)
fused_kernel(const Ptrs pt, const __grid_constant__ Maps mp) {
  extern __shared__ __align__(1024) uint8_t smem_raw[];
  const uint32_t base = smem_u32(smem_raw);
  const uint32_t bars = base + BAR_OFF;
  const int tid = threadIdx.x, lane = tid & 31;
  auto early_pf = [&](int kb) {
    const int c = blockIdx.x;
    const char* p = lane < 16 ? (const char*)pt.x + (c * 16 + lane) * 1280 + kb * 128 : (const char*)pt.wq + kb * 64 * 3840 + (c * 15 + lane - 16) * 128;
    if (lane < 31) asm volatile("prefetch.global.L2 [%0];" ::"l"(p));
  };
  if (tid < 32) early_pf(0);
  if ((tid >> 5) == 8 && elect()) { mbar_init(bars, 1); asm volatile("fence.mbarrier_init.release.cluster;" ::: "memory"); }
  __syncwarp();
  asm volatile("barrier.cluster.arrive.relaxed.aligned;" ::: "memory");
  const int warp = __shfl_sync(0xffffffffu, tid >> 5, 0);
  uint32_t r; asm("mov.u32 %0, %%cluster_ctarank;" : "=r"(r));
  auto BAR = [&](int i) { return bars + i * 8; };
  auto FULL = [&](int s) { return bars + s * 8; };
  auto EMPTY = [&](int s) { return bars + (B_EMPTY + s) * 8; };
  auto DATA = [&](int s) { return bars + (B_DATA + s) * 8; };

  const int t = (blockIdx.x >> 1) + (blockIdx.x < 8 ? 62 : -4);
  const int u7 = t - 32, q7 = (u7 * 37) >> 8;
  const int g = t < 32 ? (t & 7) : t < 60 ? 1 + u7 - 7 * q7 : 0;
  const int i = t < 32 ? (t >> 3) : t < 60 ? 4 + q7 : t - 58;
  const int qm = g * 2 + r, qj = i;

  if (warp == 8) {
    if (elect()) {
      mbar_expect_tx(FULL(0), 46 * KB);
      tma3d(base, &mp.x, 0, qm * 64, 0, FULL(0));
      asm volatile("prefetch.tensormap [%0];" ::"l"(&mp.wqm) : "memory");
      asm volatile("prefetch.tensormap [%0];" ::"l"(&mp.wqr) : "memory");
    }
    __syncwarp();
  }
  asm volatile("barrier.cluster.wait.aligned;" ::: "memory");
  if (warp == 8 && elect()) {
    tma3d_mc(base + 16 * KB + r * 16 * KB, &mp.wqm, qj * 80, r * 32, 0, FULL(0));
    tma3d_mc(base + 28 * KB + r * 16 * KB, &mp.wqr, qj * 80 + 64, r * 32, 0, FULL(0));
  }
  const uint32_t t0 = clk();
  if (warp == 8) TSG(6, 0);
  if (elect()) {
    const int b0 = warp < 8 ? warp + 2 : warp < 10 ? warp - 8 : 76 + 2 * warp;
    if (warp > 12) mbar_init(BAR(95 + warp), 4);
    if (warp != 8) mbar_init(BAR(b0), warp == 12 ? 3 : 1);
    mbar_init(BAR(b0 + (warp < 10 ? B_EMPTY : 1)), (0x4111114444444444ull >> (4 * warp)) & 15);
    asm volatile("fence.mbarrier_init.release.cluster;" ::: "memory");
  }
  __syncwarp();
  asm volatile("barrier.cluster.arrive.relaxed.aligned;" ::: "memory");
  asm volatile("barrier.cluster.wait.aligned;" ::: "memory");
  const bool hasG = g || i < 4;
  const int gn = (2 * g - (i >> 2)) * 4 + (i & 3), g3 = ((gn - 24) * 43) >> 7;
  const int gf = !hasG ? 0 : gn < 24 ? gn >> 1 : 11 - g3, gd = gn < 24 ? gn & 1 : gn - 22 - 3 * g3;
  const int pm = g * 2 + (i >> 2), pn = i & 3;

  unsigned* const epp = pt.sc->cnt + (C_EP + g * 16 + i * 2 + r) * 32;
  auto dep_load = [&](int n, int sl, int par) {
    const bool po = n < NPO;
    mbar_expect_tx(DATA(SP + n), po ? 16 * KB : 20 * KB);
    tma2d(base + (po ? pa_off(sl) : pb_off(sl)), po ? &mp.old_ : &mp.uld, (po ? r * 320 : r * 768 - NPO * 64) + n * 64, po ? pm * 128 + par * S_ : pn * 160 + par * D_, DATA(SP + n));
  };

  if (warp < 8) {
    asm volatile("setmaxnreg.inc.sync.aligned.u32 216;");
    if (warp == 1) early_pf(1);
    const int wg = warp >> 2, w = warp & 3;
    const bool lead = (tid & 127) == 0;
    const bool keeper = (wg == (int)r);
    const int rho = lane >> 2, q = lane & 3;
    const uint32_t dbase = (base & 0x3FFFF) >> 4, dwg = dbase + wg * (8 * KB >> 4);
    float accG[64];
    const uint32_t dsend = dbase, dkeep = dbase + 512;
    auto g_issue = [&](int n, bool wait = true) {
      if (wait) mbar_wait(FULL(NQ + n));
      TSG(0, 64 + (wg ^ (int)r) * 64 + NQ + n);
      const uint32_t o = g_off(n) >> 4;
      wg_fence();
#pragma unroll
      for (int k = 0; k < 4; k++)
        Wgmma<128, 1, 1, H128, H128>::run(accG, dwg + o + dlo(16 * KB + k * 2048, 8192), dbase + o + dlo(k * 2048, 8192), (n | k) != 0);
      wg_commit();
    };
    auto g_step = [&](int n) {
      g_issue(n);
      wg_wait<1>();
      if (lead) mbar_arrive(EMPTY(NQ + n - 1));
    };
    uint32_t Qp[10][2], Kp[10][2], Vt[10][2];
    {
      float acc[96], acr[24];
      const uint32_t rempty = mapa(EMPTY(0), r ^ 1);
#pragma unroll 1
      for (int s = 0; s < NQ; s++) {
        mbar_wait(FULL(s));
        TSG(0, 64 + (wg ^ (int)r) * 64 + s);
        const uint32_t o = q_off(s) >> 4;
        wg_fence();
#pragma unroll
        for (int k = 0; k < 4; k++) {
          Wgmma<48, 0, 1, H128, H32>::run(acr, dwg + o + dlo(k * 32, 16), dbase + o + dlo(28 * KB + (k >> 1) * 16 * KB + (k & 1) * 512, 1024), (s | k) != 0);
          Wgmma<192, 0, 1, H128, H128>::run(acc, dwg + o + dlo(k * 32, 16), dbase + o + dlo(16 * KB + (k >> 1) * 16 * KB + (k & 1) * 2048, 4096), (s | k) != 0);
        }
        wg_commit();
        wg_wait<1>();
        if (s > 0 && lead) { mbar_arrive(EMPTY(s - 1)); mbar_arrive_remote(rempty + (s - 1) * 8); }
      }
      bar_sync<1, 256>();
      g_issue(0);
      wg_wait<1>();
      reg_fence(acc); reg_fence(acr);
      if (lead) { mbar_arrive(EMPTY(NQ - 1)); mbar_arrive_remote(rempty + (NQ - 1) * 8); }
      TSG(1, 17 + (wg ^ (int)r) * 16);
#pragma unroll
      for (int c = 0; c < 10; c++) {
        const float* ak = c < 8 ? acc + 4 * (8 + c) : acr + 4 * (c - 6);
        const float* av = c < 8 ? acc + 4 * (16 + c) : acr + 4 * (c - 4);
        Kp[c][1] = pack2(ak[2], ak[3]); Vt[c][1] = movm(pack2(av[2], av[3]));
      }
      mbar_wait(BAR(B_LNDONE));
      const uint32_t dst = base + HALO_OFF + (w == 3 ? 8 + wg : warp + 1) * 2560;
#pragma unroll
      for (int c = 0; c < 2; c++) {
        sts128(dst + c * 1280 + lane * 16, Kp[5 * c][1], Kp[5 * c + 1][1], Kp[5 * c + 3][1], Kp[5 * c + 4][1]);
        sts128(dst + c * 1280 + 512 + lane * 16, Kp[5 * c + 2][1], Vt[5 * c][1], Vt[5 * c + 1][1], Vt[5 * c + 2][1]);
        sts64(dst + c * 1280 + 1024 + lane * 8, Vt[5 * c + 3][1], Vt[5 * c + 4][1]);
      }
      bar_arrive<8, 288>();
      g_step(1);
#pragma unroll
      for (int c = 0; c < 10; c++) {
        float* aq = c < 8 ? acc + 4 * c : acr + 4 * (c - 8);
        float* ak = c < 8 ? acc + 4 * (8 + c) : acr + 4 * (c - 6);
        float* av = c < 8 ? acc + 4 * (16 + c) : acr + 4 * (c - 4);
        asm volatile("" : "+f"(aq[0]), "+f"(aq[2]), "+f"(ak[0]), "+f"(av[0])::"memory");
        Qp[c][0] = pack2(aq[0], aq[1]); Qp[c][1] = pack2(aq[2], aq[3]);
        Kp[c][0] = pack2(ak[0], ak[1]); Vt[c][0] = movm(pack2(av[0], av[1]));
      }
    }
#pragma unroll 1
    for (int n = 2; n < ATT0; n++) g_step(n);
    mbar_wait(BAR(B_HALO));
    {
      const bool e0 = 2 * q > rho, e1 = 2 * q + 1 > rho, lo = q < 2;
      uint32_t maskE = (e0 ? 0xFFFFu : 0u) | (e1 ? 0xFFFF0000u : 0u);
      float neg = (qm == 0 && w == 0) ? -1e9f / 0.22360679774997896f : 0.f;
      const uint32_t hsrc = base + HALO_OFF + warp * 2560;
      uint32_t odst = base + OST_OFF + (warp * 16 + (lane & 15)) * 160 + (lane >> 4) * 16;
      uint32_t K0[10], V0[10], Qm[4][2];
#pragma unroll
      for (int c = 0; c < 2; c++) {
        const uint4 a = lds128(hsrc + c * 1280 + lane * 16), b = lds128(hsrc + c * 1280 + 512 + lane * 16);
        K0[5 * c] = a.x; K0[5 * c + 1] = a.y; K0[5 * c + 3] = a.z; K0[5 * c + 4] = a.w;
        K0[5 * c + 2] = b.x; V0[5 * c] = b.y; V0[5 * c + 1] = b.z; V0[5 * c + 2] = b.w;
        lds64(hsrc + c * 1280 + 1024 + lane * 8, V0[5 * c + 3], V0[5 * c + 4]);
      }
#pragma unroll
      for (int h = 0; h < 4; h++) {
        Qm[h][0] = (lo != (h & 1)) ? Qp[5 * (h >> 1) + 2][0] : 0u; Qm[h][1] = (lo != (h & 1)) ? Qp[5 * (h >> 1) + 2][1] : 0u;
        asm volatile("" : "+r"(Qm[h][0]), "+r"(Qm[h][1]));
      }
      asm volatile("" : "+r"(maskE), "+f"(neg), "+r"(odst));
      auto drain = [&]() {
        wg_wait<0>();
        if (lead) mbar_arrive(EMPTY(NQ + ATT0 - 1));
        mbar_wait(FULL(NQ + ATT0));
        TSG(1, 30 + (wg ^ (int)r) * 16);
      };
      float S[4][3][4], O[4][3][4], sm[4][4];
#pragma unroll
      for (int h = 0; h < 4; h++) {
        if (h == AV1) drain();
        const int G = 5 * (h >> 1) + 2, H = G - 2 + 3 * (h & 1);
        mma1688z(S[h][0], Qm[h][0], Qm[h][1], K0[G], neg); mma1688z(S[h][1], Qm[h][0], Qm[h][1], Kp[G][0]); mma1688z(S[h][2], Qm[h][0], Qm[h][1], Kp[G][1]);
        mma16816(S[h][0], Qp[H][0], Qp[H][1], Qp[H + 1][0], Qp[H + 1][1], K0[H], K0[H + 1]);
        mma16816(S[h][1], Qp[H][0], Qp[H][1], Qp[H + 1][0], Qp[H + 1][1], Kp[H][0], Kp[H + 1][0]);
        mma16816(S[h][2], Qp[H][0], Qp[H][1], Qp[H + 1][0], Qp[H + 1][1], Kp[H][1], Kp[H + 1][1]);
      }
#pragma unroll
      for (int h = 0; h < 4; h++) {
        uint32_t P0, P1;
        win_softmax(S[h], e0, e1, P0, P1);
        const int g0 = 5 * (h >> 1) + 2 * (h & 1);
        mma1688z(sm[h], P0, P1, 0x3F803F80u);
#pragma unroll
        for (int c = 0; c < 3; c++) mma1688z(O[h][c], P0 & maskE, 0u, V0[g0 + c]);
#pragma unroll
        for (int c = 0; c < 3; c++) mma16816(O[h][c], P0 & ~maskE, P1 & maskE, 0u, P1 & ~maskE, Vt[g0 + c][0], Vt[g0 + c][1]);
      }
#pragma unroll
      for (int hp = 0; hp < 2; hp++) {
        float (&A)[3][4] = O[2 * hp];
        float (&B)[3][4] = O[2 * hp + 1];
        const float a0 = rcp(sm[2 * hp][0]), a1 = rcp(sm[2 * hp][2]), b0 = rcp(sm[2 * hp + 1][0]), b1 = rcp(sm[2 * hp + 1][2]);
        stsm4(odst + hp * 80, pack2(A[0][0] * a0, A[0][1] * a0), pack2(A[0][2] * a1, A[0][3] * a1), pack2(A[1][0] * a0, A[1][1] * a0), pack2(A[1][2] * a1, A[1][3] * a1));
        stsm4(odst + hp * 80 + 48, pack2(B[1][0] * b0, B[1][1] * b0), pack2(B[1][2] * b1, B[1][3] * b1), pack2(B[2][0] * b0, B[2][1] * b0), pack2(B[2][2] * b1, B[2][3] * b1));
        const float c0 = lo ? a0 : b0, c1 = lo ? a1 : b1;
        stsm2(odst + hp * 80 + 32, pack2((lo ? A[2][0] : B[0][0]) * c0, (lo ? A[2][1] : B[0][1]) * c0), pack2((lo ? A[2][2] : B[0][2]) * c1, (lo ? A[2][3] : B[0][3]) * c1));
      }
      bar_sync<2, 288>();
    }
    TSG(1, 19 + (wg ^ (int)r) * 16);
    g_issue(ATT0, false);
    uint32_t bb[8];
    ldsm4(base + B1_OFF + (lane >> 3) * 16, bb[0], bb[1], bb[2], bb[3]);
    ldsm4(base + B1_OFF + 64 + (lane >> 3) * 16, bb[4], bb[5], bb[6], bb[7]);
#pragma unroll 1
    for (int n = ATT0 + 1; n < NG - LEADG; n++) g_step(n);
    const uint32_t rcv = base + RECV_OFF;
    {
      float accS[32], accK[32];
      mbar_wait(BAR(B_XFREE0));
#pragma unroll
      for (int n = NG - LEADG; n < NG; n++) {
        mbar_wait(FULL(NQ + n));
        TSG(0, 64 + (wg ^ (int)r) * 64 + NQ + n);
        const uint32_t o = g_off(n) >> 4;
        wg_fence();
#pragma unroll
        for (int k = 0; k < 4; k++) Wgmma<64, 1, 1, H128, H128>::run(accS, dwg + o + dlo(16 * KB + k * 2048, 8192), dsend + o + dlo(k * 2048, 8192), n != NG - LEADG || k);
        wg_commit();
        if (n == NG - LEADG) {
          wg_wait<1>(); reg_fence(accG);
          if (lead) mbar_arrive(EMPTY(NQ + n - 1));
        }
      }
      const uint32_t rdst = mapa(rcv + warp * 1024 + lane * 16, r ^ 1), rbar = mapa(BAR(B_RECVG), r ^ 1), half = 0x3F003F00u;
      TSG(2, 20 + (wg ^ (int)r) * 16);
      wg_fence();
#pragma unroll
      for (int e = 0; e < 4 * LEADG; e++) {
        const int n = NG - LEADG + (e >> 2), k = e & 3;
        Wgmma<64, 1, 1, H128, H128>::run(accK, dwg + (g_off(n) >> 4) + dlo(16 * KB + k * 2048, 8192), dkeep + (g_off(n) >> 4) + dlo(k * 2048, 8192), e);
        if (k == 0 || k == 3) wg_commit();
        if (k == 0) {
          wg_wait<1>();
          if (e == 0) reg_fence(accS); else if (lead) mbar_arrive(EMPTY(NQ + n - 1));
        }
        if (e % SDIV == 0 && e / SDIV < 4) {
          const int c = e / SDIV;
          float a[8];
#pragma unroll
          for (int f = 0; f < 8; f++) a[f] = accS[8 * c + f] + accG[8 * c + f];
          const uint32_t h0 = hmul2(bb[2 * c], half), h1 = hmul2(bb[2 * c + 1], half);
          st_async4(rdst + (c >> 1) * 8192 + (c & 1) * 512, hfma2(pack2(a[0], a[1]), half, h0), hfma2(pack2(a[2], a[3]), half, h0),
                    hfma2(pack2(a[4], a[5]), half, h1), hfma2(pack2(a[6], a[7]), half, h1), rbar + (c >> 1) * 8);
        }
      }
      wg_wait<0>();
      reg_fence(accK);
      if (lead) mbar_arrive(EMPTY(SP - 1));
      TSG(2, 21 + (wg ^ (int)r) * 16);
      uint32_t udst = rcv + (warp * 16 + (lane & 15)) * 64 + (((lane >> 4) ^ ((lane >> 1) & 3)) << 4), usrc = rcv + warp * 1024 + lane * 16;
      float a[16];
#pragma unroll
      for (int e = 0; e < 16; e++) a[e] = accK[e] + accG[32 + e];
#pragma unroll
      for (int hf = 0; hf < 2; hf++) {
        if (PEEL == 2 && hf == 0) mbar_wait(FULL(SP));
        mbar_wait(BAR(B_RECVG + hf));
        if (hf == 0) TSG(2, 22 + (wg ^ (int)r) * 16);
        const uint4 v0 = lds128(usrc), v1 = lds128(usrc + 512);
        __syncwarp();
        auto ge = [&](float a0, float a1, uint32_t p) { return pack2(gelu_half(fmaf(a0, 0.5f, bf_lo(p))), gelu_half(fmaf(a1, 0.5f, bf_hi(p)))); };
        stsm4(udst, ge(a[0], a[1], v0.x), ge(a[2], a[3], v0.y), ge(a[4], a[5], v0.z), ge(a[6], a[7], v0.w));
        stsm4(udst ^ 32, ge(a[8], a[9], v1.x), ge(a[10], a[11], v1.y), ge(a[12], a[13], v1.z), ge(a[14], a[15], v1.w));
        asm volatile("bar.arrive %0, 288;" ::"r"(3 + hf) : "memory");
        udst += 8192; usrc += 8192;
#pragma unroll
        for (int e = 0; e < 16; e++) a[e] = accK[16 + e] + accG[48 + e];
      }
    }
    TSG(2, 23 + (wg ^ (int)r) * 16);
    float accA[80];
    auto po_step = [&](int n, bool wait) {
      if (wait) mbar_wait(FULL(SP + n));
      TSG(0, 64 + (wg ^ (int)r) * 64 + SP + n);
      const uint32_t a = dwg + (pa_off(n) >> 4), b = dbase + (pb_off(n) >> 4);
      wg_fence();
#pragma unroll
      for (int k = 0; k < 4; k++) Wgmma<160, 0, 1, H128, H64>::run(accA, a + dlo(k * 32, 16), b + dlo(k * 1024, 4096), (n | k) != 0);
      wg_commit();
    };
    if (PEEL) po_step(0, PEEL == 1);
#pragma unroll 1
    for (int n = PEEL > 0; n < NPO; n++) {
      po_step(n, true);
      wg_wait<1>();
      if (lead && n) mbar_arrive(EMPTY(SP + n - 1));
    }
    TSG(2, 24 + (wg ^ (int)r) * 16);
    float3 gt0, gt1;
    asm volatile("ld.shared.v2.f32 {%0,%1}, [%6];\nld.shared.f32 %2, [%6+8];\nld.shared.v2.f32 {%3,%4}, [%6+256];\nld.shared.f32 %5, [%6+264];"
                 : "=f"(gt0.x), "=f"(gt0.y), "=f"(gt0.z), "=f"(gt1.x), "=f"(gt1.y), "=f"(gt1.z) : "r"(base + GATE_OFF + (warp * 16 + rho) * 32) : "memory");
    float accY[80];
    auto py_mma = [&](int sl, bool acc) {
      const uint32_t a = dwg + (pa_off(sl) >> 4), b = dbase + (pb_off(sl) >> 4);
#pragma unroll
      for (int k = 0; k < 4; k++) Wgmma<160, 1, 0, H128, H128>::run(accY, a + dlo(k * 2048, 8192), b + dlo(k * 32, 16), acc || k != 0);
      wg_commit();
    };
    auto py_step = [&](int n, int sl) {
      mbar_wait(FULL(SP + n));
      TSG(0, 64 + (wg ^ (int)r) * 64 + SP + n);
      if (EARV && n == NP - 1) bar_arrive<10, 256>();
      wg_fence();
      py_mma(sl, n != NPO);
      if (!EARV && n == NP - 1) bar_arrive<10, 256>();
      wg_wait<1>();
      if (lead) mbar_arrive(EMPTY(SP + n - 1));
    };
    py_step(NPO, 0);
    reg_fence(accA);
    {
      const float c0 = keeper ? gt0.z : 0.f, c1 = keeper ? gt1.z : 0.f;
#pragma unroll
      for (int e = 0; e < 80; e++) accA[e] = (e & 2) ? fmaf(gt1.x, accA[e], c1) : fmaf(gt0.x, accA[e], c0);
      reg_fence(accA);
    }
    {
      int sl = 1;
#pragma unroll 1
      for (int n = NPO + 1; n < NP - (keeper ? LEADP : 0); n++) {
        py_step(n, sl);
        sl = sl == 4 ? 0 : sl + 1;
      }
    }
    if (keeper) {
      wg_wait<0>();
      if (lead) mbar_arrive(EMPTY(NSTEP - LEADP - 1));
      bar_sync<10, 256>();
      TSG(0, 64 + NSTEP - LEADP);
#pragma unroll 1
      for (int n = NP - LEADP; n < NP; n++) { wg_fence(); py_mma(n < 15 ? n - 10 : n - 15, true); }
    }
    if (!keeper) mbar_wait(BAR(B_XFREE));
    TSG(3, 25 + (wg ^ (int)r) * 16);
    wg_wait<0>();
    reg_fence(accY);
    TSG(3, 26 + (wg ^ (int)r) * 16);
    auto mix = [&](int e) {
      const float om = (e & 1) ? gt1.y : gt0.y;
      return pack2(fmaf(om, accY[2 * e], accA[2 * e]), fmaf(om, accY[2 * e + 1], accA[2 * e + 1]));
    };
    const uint32_t xch = rcv + w * 1024 + lane * 16;
    const uint32_t rdst = mapa(xch, r ^ 1), rbar = mapa(BAR(B_RECVP), r ^ 1);
    const uint32_t odst = base + RECV_OFF + (w * 16 + (lane & 15)) * 64 + (((lane >> 4) ^ ((lane >> 1) & 3)) << 4);
#pragma unroll
    for (int c = 0; c < 5; c++) {
      uint32_t pk[8];
      uint4 v0, v1;
      if (keeper) { mbar_wait(BAR(B_RECVP + c)); v0 = lds128(xch + c * 4096); v1 = lds128(xch + c * 4096 + 512); __syncwarp(); }
      if (c == 0) TSG(3, 27 + (wg ^ (int)r) * 16);
#pragma unroll
      for (int e = 0; e < 8; e++) pk[e] = mix(8 * c + e);
      if (keeper) {
        stsm4(odst + c * 4096, hadd2(pk[0], v0.x), hadd2(pk[1], v0.y), hadd2(pk[2], v0.z), hadd2(pk[3], v0.w));
        stsm4((odst ^ 32) + c * 4096, hadd2(pk[4], v1.x), hadd2(pk[5], v1.y), hadd2(pk[6], v1.z), hadd2(pk[7], v1.w));
        asm volatile("bar.arrive %0, 160;" ::"r"(11 + c) : "memory");
      } else {
        st_async4(rdst + c * 4096, pk[0], pk[1], pk[2], pk[3], rbar + c * 8);
        st_async4(rdst + c * 4096 + 512, pk[4], pk[5], pk[6], pk[7], rbar + c * 8);
      }
    }
    TSG(3, 28 + (wg ^ (int)r) * 16);
  } else if (warp >= 12) {
    asm volatile("setmaxnreg.dec.sync.aligned.u32 48;");
    const int lw = warp - 12;
    const int row = r * 1024 + lw * 64 + g * 8 + i;
    uint2 gw[5], xn[5];
#pragma unroll
    for (int c = 0; c < 5; c++) gw[c] = ldg64((const uint2*)pt.gw + c * 32 + lane);
    wait_until(t0 + LNDELAY);
    const uint2* xp = (const uint2*)(pt.x + (size_t)row * D_) + lane;
#pragma unroll 1
    for (int k = -1; k < 4; k++) {
      uint32_t xv[10];
#pragma unroll
      for (int c = 0; c < 5; c++) { xv[2 * c] = xn[c].x; xv[2 * c + 1] = xn[c].y; }
      if (k < 3) {
#pragma unroll
        for (int c = 0; c < 5; c++) xn[c] = ldg64(xp + c * 32);
        xp += 256 * D_ / 4;
      }
      const uint32_t st = base + hst_off(k) + lw * HPITCH;
      if (k >= 0) {
        float sx = 0.f, q0 = 0.f, q1 = 0.f, sz = 0.f;
#pragma unroll
        for (int c = 0; c < 10; c++) {
          const float lo = bf_lo(xv[c]), hi = bf_hi(xv[c]);
          const uint32_t p = hmul2(xv[c], (c & 1) ? gw[c >> 1].y : gw[c >> 1].x);
          sx += lo + hi; q0 = fmaf(lo, lo, q0); q1 = fmaf(hi, hi, q1); sz += bf_lo(p) + bf_hi(p);
        }
        float sq = q0 + q1;
#pragma unroll
        for (int o = 1; o < 32; o <<= 1) { sx += __shfl_xor_sync(0xffffffffu, sx, o); sq += __shfl_xor_sync(0xffffffffu, sq, o); sz += __shfl_xor_sync(0xffffffffu, sz, o); }
        const float mean = sx * (1.f / D_), var = fmaxf(fmaf(-mean, mean, sq * (1.f / D_)), 0.f);
        float sd;
        asm("sqrt.approx.ftz.f32 %0, %1;" : "=f"(sd) : "f"(bf_round(bf_round(var) + 1e-5f)));
        const float rs = rcp(bf_round(sd)), rh = bf_round(rs);
        const uint32_t r1 = pack2(rh, rh), r2 = pack2(rs - rh, rs - rh), mb = pack2(mean, mean);
        const float gg = bf_round(rcp(1.f + ex2(-1.4426950408889634f * bf_round(sz)))), om = bf_round(1.f - gg);
#pragma unroll
        for (int c = 0; c < 5; c++) {
          const uint32_t a = hsub2(xv[2 * c], mb), b = hsub2(xv[2 * c + 1], mb);
          sts64(st + c * 256 + lane * 8, hfma2(a, r1, hmul2(a, r2)), hfma2(b, r1, hmul2(b, r2)));
        }
        if (lane == 0) sts64(base + GST_OFF + (k * 4 + lw) * 8, __float_as_uint(gg), __float_as_uint(om));
        __syncwarp();
        if (lane == 0) mbar_arrive(BAR(B_LNROW + k));
      }
    }
    mbar_wait(BAR(B_HROW0));
    const unsigned ep = __shfl_sync(0xffffffffu, lds32(BAR(EPOCH)), 0);
    mbar_wait(FULL(4));
    if (lw == 0 || lw == 3) {
      if (lw == 3 && elect()) {
        asm volatile("mbarrier.expect_tx.relaxed.cta.shared::cta.b64 [%0], 128;" ::"r"(BAR(B_HALO)) : "memory");
        bulk_ld(base + B1_OFF, pt.b1 + gf * 128 + (r ^ 1) * 64, 128, BAR(B_HALO));
      }
      __syncwarp();
      const uint4* src = pt.sc->halo + ((ep & 1) * 136 + qm * 8 + qj) * 320 + (lw & 1) * 160 + lane;
      if (ep == 1) mbar_wait(BAR(B_HREADY + 1));
      mbar_wait(EMPTY(NQ + HG));
      TSG(4, 9);
      uint4 v[5];
      while (true) {
#pragma unroll
        for (int c = 0; c < 5; c++) asm volatile("ld.relaxed.gpu.global.v4.u32 {%0,%1,%2,%3}, [%4];" : "=r"(v[c].x), "=r"(v[c].y), "=r"(v[c].z), "=r"(v[c].w) : "l"(src + c * 32) : "memory");
        if (!__any_sync(0xffffffffu, max(max(max(v[0].w, v[1].w), max(v[2].w, v[3].w)), v[4].w) == ~0u)) break;
        __nanosleep(RGAP);
      }
#pragma unroll
      for (int c = 0; c < 5; c++) sts128(base + HALO_OFF + (lw & 1) * 4 * 2560 + c * 512 + lane * 16, v[c].x, v[c].y, v[c].z, v[c].w);
      __syncwarp();
      if (lane == 0) mbar_arrive(BAR(B_HALO));
      TSG(4, 14);
    }
    if (lw == 1 || lw == 2) {
      int sl = lw - 1;
      const uint32_t last = base + lane * 128 + ((lane & 7) ^ 7) * 16 + 12;
#pragma unroll 1
      for (int n = lw - 1; n < NP; n += 2) {
        const bool po = n < NPO;
        const uint32_t a = last + (po ? pa_off(sl) : pb_off(sl));
        const uint32_t b = po ? a ^ (((8 - 2 * n) & 6) << 4) : a + 4096;
        for (uint32_t par = 0;; par ^= 1) {
          mbar_wait_par(DATA(SP + n), par);
          uint32_t m = max(max(max(lds32(a), lds32(a + 4096)), max(lds32(a + 8192), lds32(a + 12288))), lds32(b + 12288));
          if (po) m = max(max(m, lds32(b)), max(lds32(b + 4096), lds32(b + 8192)));
          if (!__any_sync(0xffffffffu, m == ~0u)) break;
          __nanosleep(RGAP);
          if (elect()) dep_load(n, sl, ep & 1);
          __syncwarp();
        }
        if (lane == 0) mbar_arrive(FULL(SP + n));
        sl = sl >= 3 ? sl - 3 : sl + 2;
      }
    }
  } else {
    asm volatile("setmaxnreg.dec.sync.aligned.u32 32;");
    if (warp > 8) {
      unsigned* cnt = pt.sc->cnt;
      const unsigned ep0 = ld_relaxed(epp);
      const bool one = elect();
      if (one) {
#pragma unroll 1
        for (int s = NQ + warp - 9; s < NSTEP + 5; s += 3) { mbar_init(FULL(s), 2); mbar_init(EMPTY(s), 2); mbar_init(DATA(s), 1); }
        fence_async_smem();
      }
      __syncwarp();
      bar_arrive<5, 128>();
      const unsigned ep = __shfl_sync(0xffffffffu, ep0, 0) + 1;
      if (warp == 9) {
        const int row0 = r * 1024 + g * 8 + i;
#pragma unroll 1
        for (int pass = ep == 1 ? 0 : 1; pass < 2; pass++) {
          if (pass) {
            __nv_bfloat16* hp = pt.sc->h + (size_t)row0 * D_;
            const float b2v = __bfloat162float(pt.b2[row0 + (lane >> 1) * 64]);
#pragma unroll 1
            for (int k = 0; k < 4; k++) {
              mbar_wait(BAR(B_LNROW + k));
              if (one) {
                fence_async_smem();
#pragma unroll
                for (int j = 0; j < 4; j++) bulk_st(hp + (k * 4 + j) * 64 * D_, base + hst_off(k) + j * 1280, 1280);
                bulk_commit();
                if (k == 1) { bulk_wait0(); sts64(BAR(EPOCH), ep, 0); mbar_arrive(BAR(B_HROW0)); }
              }
              __syncwarp();
            }
            {
              uint32_t gg, om;
              lds64(base + GST_OFF + (lane >> 1) * 8, gg, om);
              pt.sc->gate[(row0 + (lane >> 1) * 64) * 2 + (lane & 1)] = make_float4(__uint_as_float(gg), __uint_as_float(om), __uint_as_float(om) * b2v, 0.f);
            }
            __syncwarp();
            if (one) {
              bulk_wait0();
              mbar_arrive(BAR(B_LNDONE));
              TSG(4, 0);
              asm volatile("red.release.gpu.global.add.u32 [%0], 1;" ::"l"(cnt + (C_H + 4 + (i & 3)) * 32) : "memory");
              TSG(4, 8);
            }
            mbar_wait(FULL(4));
          }
          const int par = (ep ^ pass) & 1;
          const uint4 mark = make_uint4(~0u, ~0u, ~0u, ~0u);
          uint4* po = (uint4*)(pt.sc->o + (size_t)(par * S_ + qm * 128 + (lane >> 2)) * D_ + ((lane & 2) ? qj * 80 + 64 : ((qj * 5 + 4) >> 2) * 64 - 16)) + (lane & 1);
          uint4* pu = (uint4*)(pt.sc->u + (size_t)(par * D_ + gd * 128 + (lane >> 1)) * F_ + (gf * 2 + r) * 64 + 48) + (lane & 1);
          uint4* ph = pt.sc->halo + (par * 136 + qm * 8 + qj + 8) * 320 + (lane >> 1) * 8 + 6 + (lane & 1);
#pragma unroll 1
          for (int k = 0; k < 9; k++) {
            for (int n = 0; pass && !mbar_try(k < 8 ? EMPTY(PST + k) : BAR(B_RECVP + 4)); n++) {
              __nanosleep(60);
              if (n > (1 << 24)) asm volatile("st.global.u32 [%0], 0;" ::"l"((char*)pt.sc + 1) : "memory");
            }
            if (k == 8) break;
            if (pass && k == 0) *epp = ep;
            po[0] = mark; po[D_] = mark; po += 2 * D_;
            if (hasG) *pu = mark;
            pu += 2 * F_;
            if (k < 3) ph[k * 96] = mark;
          }
          if (!pass) __threadfence();
          __syncwarp();
        }
      } else if (warp == 11) {
        mbar_wait(FULL(1));
        if (one) {
          mbar_expect_tx(BAR(B_RECVG), 8 * KB); mbar_expect_tx(BAR(B_RECVG + 1), 8 * KB);
#pragma unroll 1
          for (int k = 0; k < 9; k++) asm volatile("prefetch.tensormap [%0];" ::"l"(&mp.h + k) : "memory");
        }
#pragma unroll 1
        for (int j = 0; j < 2; j++) {
          mbar_wait(BAR(j ? B_LNDONE : B_HROW0));
          __nanosleep(HSLP);
          while (!__all_sync(0xffffffffu, (int)(ld_acquire(cnt + (C_H + (j ? 4 + (lane & 3) : r * 2 + (lane & 1))) * 32) - ep * 32) >= 0)) {}
          asm volatile("fence.proxy.async.global;" ::: "memory");
          if (one) mbar_arrive(BAR(B_HREADY + j));
          TSG(4, 2 - j);
        }
        if (one) {
          mbar_wait(BAR(B_OFREE));
          asm volatile("mbarrier.expect_tx.relaxed.cta.shared::cta.b64 [%0], 4096;" ::"r"(FULL(SP)) : "memory");
          bulk_ld(base + GATE_OFF, pt.sc->gate + pm * 256, 4096, FULL(SP));
          TSG(4, 4);
          int sl = 0; uint32_t tl = t0;
#pragma unroll 1
          for (int n = 0; n < NP; n++) {
            mbar_wait(EMPTY(n < 2 ? 21 : n == 3 ? 23 : n + 21));
            if (n == NPO) { await(cnt + (C_U + r * 2) * 32, ep * 5 * U0); TSG(4, 6); }
            if (n == NPO + U0) mbar_wait(BAR(B_UREADY));
            wait_until(tl + (n < NPO ? PSTAG : USTAG));
            tl = clk();
            dep_load(n, sl, ep & 1);
            sl = sl == 4 ? 0 : sl + 1;
            TSG(5, 192 + SP + n);
          }
        }
      } else {
        if (one) {
          mbar_wait(BAR(B_HROW0));
          asm volatile("red.release.gpu.global.add.u32 [%0], 1;" ::"l"(cnt + (C_H + r * 2 + (i & 1)) * 32) : "memory");
          bar_sync<8, 288>();
          fence_async_smem();
          bulk_st(pt.sc->halo + ((ep & 1) * 136 + qm * 8 + qj + 8) * 320, base + HALO_OFF + 8 * 2560, 5120);
          mbar_arrive(BAR(B_HALO));
          TSG(4, 15);
          bar_sync<2, 288>();
          fence_async_smem();
          TSG(4, 7);
          tma3d_st(&mp.ost, qj * 80, qm * 64 + (ep & 1) * 1024, 0, base + OST_OFF);
          bulk_commit(); bulk_wait0();
          mbar_arrive(BAR(B_OFREE));
          mbar_wait(EMPTY(NQ + 8));
          mbar_arrive_remote(mapa(BAR(B_XFREE0), r ^ 1));
          TSG(4, 10);
#pragma unroll 1
          for (int hf = 0; hf < 2; hf++) {
            asm volatile("bar.sync %0, 288;" ::"r"(3 + hf) : "memory");
            fence_async_smem();
            TSG(4, 11 + hf);
            if (hasG) tma2d_st(&mp.ust, (gf * 2 + r) * 64 + hf * 32, gd * 128 + (ep & 1) * D_, base + RECV_OFF + hf * 8192);
          }
          bulk_commit(); bulk_wait0();
          const int kb = gf * 2 + r, kh = kb >= 12;
          if (hasG) hint(cnt + (C_U + kh * 2 + (kb - kh * 12 >= U0)) * 32);
          TSG(4, 13);
          await(cnt + (C_U + r * 2 + 1) * 32, ep * (60 - 5 * U0));
          mbar_arrive(BAR(B_UREADY));
          TSG(4, 5);
#pragma unroll 1
          for (int c = 0; c < 5; c++) mbar_expect_tx(BAR(B_RECVP + c), 4 * KB);
          mbar_arrive_remote(mapa(BAR(B_XFREE), r ^ 1));
#pragma unroll 1
          for (int c = 0; c < 5; c++) {
            asm volatile("bar.sync %0, 160;" ::"r"(11 + c) : "memory");
            fence_async_smem();
            tma2d_st(&mp.out, pn * 160 + c * 32, pm * 128 + r * 64, base + RECV_OFF + c * 4 * KB);
          }
          bulk_commit();
          asm volatile("cp.async.bulk.wait_group.read 0;" ::: "memory");
          TSG(3, 3);
        }
      }
    } else {
#pragma unroll 1
      for (int s = 1; s < NQ; s++) {
        const uint32_t a = base + q_off(s), b = a + 16 * KB + r * 16 * KB;
        if (s == 4) bar_sync<5, 128>();
        if (s >= 4) mbar_wait(EMPTY(s - 4));
        else wait_until(t0 + s * STAGGER);
        if (elect()) {
          mbar_expect_tx(FULL(s), 46 * KB);
          tma3d(a, &mp.x, s * 64, qm * 64, 0, FULL(s));
          tma3d_mc(b, &mp.wqm, qj * 80, s * 64 + r * 32, 0, FULL(s));
          tma3d_mc(b + 12 * KB, &mp.wqr, qj * 80 + 64, s * 64 + r * 32, 0, FULL(s));
        }
        TSG(5, 192 + s);
      }
      if (!elect()) return;
#pragma unroll 1
      for (int n = 0; n < NG; n++) {
        mbar_wait(BAR(B_HREADY + (n >> 3)));
        mbar_wait(EMPTY(n + 4 + ((0x50000156u >> (2 * n)) & 3)));
        const uint32_t a = base + g_off(n);
        mbar_arrive(FULL(NQ + n));
        if (hasG) {
          mbar_expect_tx(FULL(NQ + n), 32 * KB);
          tma2d(a, &mp.w1, gf * 128 + (r ^ 1) * 64, r * 1024 + n * 64, FULL(NQ + n));
          tma2d(a + 8 * KB, &mp.w1, gf * 128 + r * 64, r * 1024 + n * 64, FULL(NQ + n));
          tma3d(a + 16 * KB, &mp.h, 0, r * 1024 + n * 64, gd * 2, FULL(NQ + n));
        } else mbar_arrive(FULL(NQ + n));
        TSG(5, 192 + NQ + n);
        if (n == ATT0 + PFN) {
          asm volatile("cp.async.bulk.prefetch.L2.global [%0], 6400;" ::"l"(pt.wo + (g * 16 + i * 2 + r) * 3200) : "memory");
#pragma unroll 1
          for (int k = ATT0 + 6; k < NG; k++) asm volatile("cp.async.bulk.prefetch.L2.global [%0], 3072;" ::"l"(pt.w1 + (size_t)(r * 1024 + k * 64 + g * 8 + i) * F_) : "memory");
        }
      }
      mbar_wait(BAR(B_OFREE));
      int sl = 0;
      uint32_t tl = clk() - 250;
#pragma unroll 1
      for (int n = 0; n < NP; n++) {
        mbar_wait(EMPTY(n < 3 ? n + 20 : n + 21));
        wait_until(tl + PSTAG);
        tl = clk();
        const bool po = n < NPO;
        mbar_expect_tx(FULL(SP + n), po ? 20 * KB : 16 * KB);
        tma3d(base + (po ? pb_off(sl) : pa_off(sl)), po ? &mp.wo : &mp.w2, 0, (po ? r * 320 : r * 768 - NPO * 64) + n * 64, po ? pn * 5 : pm * 2, FULL(SP + n));
        sl = sl == 4 ? 0 : sl + 1;
      }
    }
  }
}

typedef CUresult (*EncFn)(CUtensorMap*, CUtensorMapDataType, cuuint32_t, void*, const cuuint64_t*, const cuuint64_t*, const cuuint32_t*,
                          const cuuint32_t*, CUtensorMapInterleave, CUtensorMapSwizzle, CUtensorMapL2promotion, CUtensorMapFloatOOBfill);

void mkmap(EncFn enc, CUtensorMap* m, const void* ptr, int rank, cuuint64_t d0, cuuint64_t d1, cuuint64_t d2, cuuint64_t s1, cuuint64_t s2,
           cuuint32_t b0, cuuint32_t b1, cuuint32_t b2, CUtensorMapSwizzle sw) {
  cuuint64_t dims[3] = {d0, d1, d2}, st[2] = {s1, s2};
  cuuint32_t box[3] = {b0, b1, b2}, es[3] = {1, 1, 1};
  enc(m, CU_TENSOR_MAP_DATA_TYPE_BFLOAT16, rank, (void*)ptr, dims, st, box, es, CU_TENSOR_MAP_INTERLEAVE_NONE, sw,
      CU_TENSOR_MAP_L2_PROMOTION_L2_128B, CU_TENSOR_MAP_FLOAT_OOB_FILL_NONE);
}

}

extern "C" void kernel_launch(void* const* d_in, const int* in_sizes, int n_in, void* d_out, int out_size) {
  (void)in_sizes; (void)n_in; (void)out_size;
  const __nv_bfloat16* x = (const __nv_bfloat16*)d_in[0];
  const __nv_bfloat16* wqkv = (const __nv_bfloat16*)d_in[1];
  const __nv_bfloat16* wo = (const __nv_bfloat16*)d_in[2];
  const __nv_bfloat16* w1 = (const __nv_bfloat16*)d_in[4];
  const __nv_bfloat16* w2 = (const __nv_bfloat16*)d_in[6];
  void* fn = nullptr; cudaDriverEntryPointQueryResult qr;
  cudaGetDriverEntryPoint("cuTensorMapEncodeTiled", &fn, cudaEnableDefault, &qr);
  EncFn enc = (EncFn)fn;
  void* psc;
  cudaGetSymbolAddress(&psc, g_sc);
  Scratch* sc = (Scratch*)psc;
  void *ph = sc->h, *po = sc->o, *pu = sc->u;
  const CUtensorMapSwizzle S128 = CU_TENSOR_MAP_SWIZZLE_128B, S64 = CU_TENSOR_MAP_SWIZZLE_64B, S0 = CU_TENSOR_MAP_SWIZZLE_NONE;
  Maps mp;
  mkmap(enc, &mp.x, x, 3, 640, 1024, 2, 2560, 1280, 64, 64, 2, S128);
  mkmap(enc, &mp.wqm, wqkv, 3, 640, 640, 3, 3840, 1280, 64, 32, 3, S128);
  mkmap(enc, &mp.wqr, wqkv, 3, 640, 640, 3, 3840, 1280, 16, 32, 3, CU_TENSOR_MAP_SWIZZLE_32B);
  mkmap(enc, &mp.h, ph, 3, 64, 2048, 10, 1280, 128, 64, 64, 2, S128);
  mkmap(enc, &mp.w1, w1, 2, 1536, 2048, 1, 3072, 0, 64, 64, 1, S128);
  mkmap(enc, &mp.old_, po, 2, 640, 4096, 1, 1280, 0, 64, 128, 1, S128);
  mkmap(enc, &mp.wo, wo, 3, 32, 640, 20, 1280, 64, 32, 64, 5, S64);
  mkmap(enc, &mp.w2, w2, 3, 64, 1536, 32, 4096, 128, 64, 64, 2, S128);
  mkmap(enc, &mp.uld, pu, 2, 1536, 1280, 1, 3072, 0, 64, 160, 1, S128);
  mkmap(enc, &mp.ost, po, 3, 640, 2048, 2, 2560, 1280, 80, 64, 2, S0);
  mkmap(enc, &mp.ust, pu, 2, 1536, 1280, 1, 3072, 0, 32, 128, 1, S64);
  mkmap(enc, &mp.out, d_out, 2, 640, 2048, 1, 1280, 0, 32, 64, 1, S64);
  Ptrs pt;
  pt.sc = sc; pt.wo = wo; pt.w1 = w1; pt.x = x; pt.wq = wqkv; pt.b1 = (const __nv_bfloat16*)d_in[5]; pt.b2 = (const __nv_bfloat16*)d_in[7]; pt.gw = (const __nv_bfloat16*)d_in[8];
  cudaFuncSetAttribute(fused_kernel, cudaFuncAttributeMaxDynamicSharedMemorySize, SMEM_BYTES);
  fused_kernel<<<128, 512, SMEM_BYTES, cudaStreamPerThread>>>(pt, mp);
}
```
